```python
import torch

def _softmax(x, axis=-1):
    return torch.softmax(x, dim=axis)
def _gelu(x):
    return torch.nn.functional.gelu(x, approximate="tanh")
def _silu(x):
    return torch.nn.functional.silu(x)
def _sigmoid(x):
    return torch.sigmoid(x)
def _layernorm(x, axis=-1, eps=1e-5):
    m = x.mean(dim=axis, keepdim=True)
    v = x.var(dim=axis, keepdim=True, unbiased=False)
    return (x - m) / torch.sqrt(v + eps)
def _scatter_add(tgt, idx, src, axis=0):
    return tgt.clone().index_add_(axis, idx, src)
def _segment_sum(src, seg, n):
    out = torch.zeros((n,) + src.shape[1:], dtype=src.dtype)
    return out.index_add_(0, seg, src)
def _pad(x, pw):
    flat = tuple(v for pair in reversed(pw) for v in pair)
    return torch.nn.functional.pad(x, flat)

kernel_name = 'sequential_preLN__ssm_conv_h3__mixer_s_mlp__prompt'

def setup_inputs():

    _w = (lambda a: (lambda t: t.to(torch.bfloat16) if t.is_floating_point() else t)(torch.as_tensor(a)))
    def _A_setup():
        B, S, D = 1, 2048, 640
        ks = 4
        return {
            "q": _w((lambda *s: torch.randn(*s, dtype=torch.bfloat16) * 0.05)(B, S, D)),
            "k": _w((lambda *s: torch.randn(*s, dtype=torch.bfloat16) * 0.4)(B, S, D)),
            "v": _w((lambda *s: torch.randn(*s, dtype=torch.bfloat16) * 0.4)(B, S, D)),
            "shift_k": _w((lambda *s: torch.randn(*s, dtype=torch.bfloat16) * 0.4)(D, ks) * 0.5),
            "ssm_k": _w((lambda *s: torch.randn(*s, dtype=torch.bfloat16) * 0.4)(D, S) * (1.0 / S ** 0.5)),
            "ssm_D": _w((lambda *s: torch.randn(*s, dtype=torch.bfloat16) * 0.4)(D)),
        }
    _A_in = _A_setup()

    def _B_setup():
        B, S, D, F = 1, 2048, 640, 1728
        return {
            "x":  _w((lambda *s: torch.randn(*s, dtype=torch.bfloat16) * 0.05)(B, S, D)),
            "w1": _w((lambda *s: torch.randn(*s, dtype=torch.bfloat16) * 3.2)(D, D) * (D ** -0.5)),
            "w2": _w((lambda *s: torch.randn(*s, dtype=torch.bfloat16) * 3.2)(D, D) * (D ** -0.5)),
            "w3": _w((lambda *s: torch.randn(*s, dtype=torch.bfloat16) * 3.2)(D, F) * (D ** -0.5)),
            "w4": _w((lambda *s: torch.randn(*s, dtype=torch.bfloat16) * 3.2)(F, D) * (F ** -0.5)),
        }
    _B_in = _B_setup()

    return {
        "A_q": _A_in["q"],
        "A_k": _A_in["k"],
        "A_v": _A_in["v"],
        "A_shift_k": _A_in["shift_k"],
        "A_ssm_k": _A_in["ssm_k"],
        "A_ssm_D": _A_in["ssm_D"],
        "B_x": _B_in["x"],
        "B_w1": _B_in["w1"],
        "B_w2": _B_in["w2"],
        "B_w3": _B_in["w3"],
        "B_w4": _B_in["w4"],
    }

def reference(A_q, A_k, A_v, A_shift_k, A_ssm_k, A_ssm_D, B_x, B_w1, B_w2, B_w3, B_w4):
    def _A_ref(q, k, v, shift_k, ssm_k, ssm_D):
        B, S, D = q.shape
        ks = shift_k.shape[-1]
        k_pad = _pad(k, ((0, 0), (ks - 1, 0), (0, 0)))
        k_shift = torch.zeros_like(k)
        for t in range(ks):
            k_shift = k_shift + k_pad[:, t:t + S, :] * shift_k[:, ks - 1 - t][None, None, :]
        kv = k_shift * v
        L = 2 * S
        kv_pad = _pad(kv, ((0, 0), (0, S), (0, 0)))
        kf_pad = _pad(ssm_k, ((0, 0), (0, S)))
        kv_f = (lambda x, axes=(-2,-1): torch.fft.rfft2(x.float(), dim=axes))(kv_pad[:, None, :, :], axes=(1, 2))
        kf_f = (lambda x, axes=(-2,-1): torch.fft.rfft2(x.float(), dim=axes))(kf_pad[:, None, :], axes=(1, 2))
        kf_f = (lambda x, *d: x.permute(*d))(kf_f, 1, 2, 0)
        y_f = kv_f * kf_f[None, :, :, :]
        y = (lambda x, s, axes=(-2,-1): torch.fft.irfft2(x, s=s, dim=axes).to(torch.bfloat16))(y_f, (1, L), axes=(1, 2))[:, 0, :S, :]
        y = y + kv * ssm_D[None, None, :]
        return q * y

    def _B_ref(x, w1, w2, w3, w4):
        B, S, D = x.shape
        h = _gelu(_layernorm(x, axis=-1) @ w1)
        c = D // 4
        g0 = _pad(h[:, :, 0*c:1*c], ((0, 0), (1, 0), (0, 0)))[:, :S, :]
        g1 = _pad(h[:, :, 1*c:2*c], ((0, 0), (0, 1), (0, 0)))[:, 1:, :]
        g2 = _pad(h[:, :, 2*c:3*c], ((0, 0), (2, 0), (0, 0)))[:, :S, :]
        g3 = _pad(h[:, :, 3*c:   ], ((0, 0), (0, 2), (0, 0)))[:, 2:, :]
        hs = torch.concatenate([g0, g1, g2, g3], axis=-1) @ w2
        x1 = x + hs
        h2 = _gelu(_layernorm(x1, axis=-1) @ w3) @ w4
        return x1 + h2

    x = A_q
    h = x + _A_ref(_layernorm(x, axis=-1), A_k, A_v, A_shift_k, A_ssm_k, A_ssm_D)
    h2 = h + _B_ref(_layernorm(h, axis=-1), B_w1, B_w2, B_w3, B_w4)
    return h2
```

```cpp
#include <cuda_runtime.h>
#include <cuda_bf16.h>
#include <cuda.h>
#include <stdint.h>

namespace {

constexpr int S_ = 2048, D_ = 640, F_ = 1728;
constexpr int NCTA = 132;
constexpr int NTHR = 512;
constexpr int TT = 80;
constexpr int TT3 = 152;
constexpr float EPS = 1e-5f;

constexpr uint32_t XR = 0;
constexpr uint32_t WR = 102400;
constexpr uint32_t CR = 176128;
constexpr int NW = 9;
constexpr uint32_t TAB_STRIDE = 8320;
constexpr uint32_t TAB_E = 3 * 4, TAB_O = 1044 * 4;
constexpr uint32_t U_OFF = 41600, U_STRIDE = 4224;
constexpr uint32_t QC_OFF = 63488;
constexpr uint32_t QC5 = CR + 36864;
constexpr uint32_t KVST = 63488;
constexpr uint32_t QCST = CR;
constexpr uint32_t PIN = WR;
constexpr uint32_t PITCH = 1296;
constexpr uint32_t EXCH = CR;
constexpr uint32_t GST = CR;
constexpr uint32_t MISC = CR + 45056;
constexpr uint32_t BARS = MISC;
constexpr uint32_t ROWST = MISC + 512;
constexpr uint32_t TOKST = MISC + 1024;
constexpr uint32_t ST3 = MISC + 2560;
constexpr uint32_t SMEM_BYTES = 232448;
enum { B_KV = 0, B_X, B_PRE, B_CONV, B_CS, B_TOK, B_ST3, B_XFREE, B_U = 8  , B_QC = 13  , B_WF = 18  , B_WE = 27  ,
       B_XF = 36  , B_XE = 46  , B_X3E = 56  , B_NUM = 61 };
enum { F_P = 0, F_C = 1  , F_1 = 6, F_2, F_S, F_3, F_NUM };

struct Params {
  CUtensorMap w1, w2, w3, w4, kvT, qc, hT, hsS, hsL, x1S, x1L, HS, HL, outS;
  const __nv_bfloat16 *x, *k, *v, *shift_k, *ssm_k, *ssm_D, *pw1, *pw2, *pw3, *pw4;
};

}

__device__ __align__(1024) __nv_bfloat16 g_kvT[D_ * S_];
__device__ __align__(1024) __nv_bfloat16 g_qc[D_ * S_ * 2];
__device__ __align__(1024) __nv_bfloat16 g_hT[26 * D_ * TT];
__device__ __align__(1024) __nv_bfloat16 g_hs[(S_ + 2) * D_];
__device__ __align__(1024) __nv_bfloat16 g_x1[S_ * D_];
__device__ __align__(1024) __nv_bfloat16 g_H[S_ * F_];
__device__ __align__(1024) float2 g_st[S_ * 10];
__device__ __align__(1024) float g_cs1[D_];
__device__ __align__(1024) float g_cs3[F_];
__device__ __align__(1024) unsigned g_flag[F_NUM * 32];
__device__ unsigned g_epoch;
#define STAMP(i) do {} while (0)

namespace {

__device__ __forceinline__ void mbar_init(uint32_t b, uint32_t c) { asm volatile("mbarrier.init.shared::cta.b64 [%0], %1;" ::"r"(b), "r"(c)); }
__device__ __forceinline__ void mbar_expect(uint32_t b, uint32_t bytes) {
  asm volatile("mbarrier.arrive.expect_tx.shared::cta.b64 _, [%0], %1;" ::"r"(b), "r"(bytes) : "memory");
}
__device__ __forceinline__ void mbar_arrive(uint32_t b) { asm volatile("mbarrier.arrive.shared::cta.b64 _, [%0];" ::"r"(b) : "memory"); }
__device__ __forceinline__ void mbar_wait(uint32_t b, uint32_t par) {
  uint32_t ok;
  asm volatile(
      "{.reg .pred p; .reg .u32 c; mov.u32 c, 0;\n"
      "WL: mbarrier.try_wait.parity.shared::cta.b64 p, [%1], %2;\n"
      "@p bra WD;\n"
      "add.u32 c, c, 1; setp.lt.u32 p, c, 4000000; @p bra WL; trap;\n"
      "WD: mov.u32 %0, 1;}"
      : "=r"(ok) : "r"(b), "r"(par) : "memory");
}
__device__ __forceinline__ void poll_flag(const unsigned* f, unsigned target) {
  unsigned v;
  int it = 0;
  do {
    asm volatile("ld.relaxed.gpu.global.u32 %0, [%1];" : "=r"(v) : "l"(f) : "memory");
    if (++it > 4000000) __trap();
  } while ((int)(v - target) < 0);
  asm volatile("fence.proxy.async.global;" ::: "memory");
}
__device__ __forceinline__ void flag_add(unsigned* f) { asm volatile("red.relaxed.gpu.global.add.u32 [%0], 1;" ::"l"(f) : "memory"); }
__device__ __forceinline__ void flag_add_release(unsigned* f) { asm volatile("red.release.gpu.global.add.u32 [%0], 1;" ::"l"(f) : "memory"); }
__device__ __forceinline__ void bulk_load(uint32_t dst, const void* src, uint32_t bytes, uint32_t bar) {
  asm volatile("cp.async.bulk.shared::cluster.global.mbarrier::complete_tx::bytes [%0], [%1], %2, [%3];" ::"r"(dst), "l"(src), "r"(bytes), "r"(bar) : "memory");
}
__device__ __forceinline__ void tma_load2(uint32_t dst, const CUtensorMap* tm, int c0, int c1, uint32_t bar) {
  asm volatile("cp.async.bulk.tensor.2d.shared::cluster.global.mbarrier::complete_tx::bytes [%0], [%1, {%3,%4}], [%2];" ::"r"(dst), "l"(tm), "r"(bar), "r"(c0), "r"(c1) : "memory");
}
__device__ __forceinline__ void tma_store2(const CUtensorMap* tm, int c0, int c1, uint32_t src) {
  asm volatile("cp.async.bulk.tensor.2d.global.shared::cta.bulk_group [%0, {%2,%3}], [%1];" ::"l"(tm), "r"(src), "r"(c0), "r"(c1) : "memory");
}
__device__ __forceinline__ void tma_store5(const CUtensorMap* tm, int c0, int c1, int c2, int c3, int c4, uint32_t src) {
  asm volatile("cp.async.bulk.tensor.5d.global.shared::cta.bulk_group [%0, {%2,%3,%4,%5,%6}], [%1];" ::"l"(tm), "r"(src), "r"(c0), "r"(c1), "r"(c2), "r"(c3), "r"(c4) : "memory");
}
__device__ __forceinline__ void store_commit_wait() {
  asm volatile("cp.async.bulk.commit_group;" ::: "memory");
  asm volatile("cp.async.bulk.wait_group 0;" ::: "memory");
}
__device__ __forceinline__ void l2_prefetch(const void* p, uint32_t bytes) { asm volatile("cp.async.bulk.prefetch.L2.global [%0], %1;" ::"l"(p), "r"(bytes) : "memory"); }
__device__ __forceinline__ void fence_async_smem() { asm volatile("fence.proxy.async.shared::cta;" ::: "memory"); }
__device__ __forceinline__ void bar_sync(int id, int n) { asm volatile("bar.sync %0, %1;" ::"r"(id), "r"(n) : "memory"); }
__device__ __forceinline__ void bar_arrive(int id, int n) { asm volatile("bar.arrive %0, %1;" ::"r"(id), "r"(n) : "memory"); }
__device__ __forceinline__ uint32_t lds32(uint32_t a) { uint32_t v; asm volatile("ld.shared.b32 %0, [%1];" : "=r"(v) : "r"(a) : "memory"); return v; }
__device__ __forceinline__ float2 lds64f(uint32_t a) { float2 v; asm volatile("ld.shared.v2.f32 {%0,%1}, [%2];" : "=f"(v.x), "=f"(v.y) : "r"(a) : "memory"); return v; }
__device__ __forceinline__ uint4 lds128(uint32_t a) { uint4 v; asm volatile("ld.shared.v4.b32 {%0,%1,%2,%3}, [%4];" : "=r"(v.x), "=r"(v.y), "=r"(v.z), "=r"(v.w) : "r"(a) : "memory"); return v; }
__device__ __forceinline__ float4 lds128f(uint32_t a) { float4 v; asm volatile("ld.shared.v4.f32 {%0,%1,%2,%3}, [%4];" : "=f"(v.x), "=f"(v.y), "=f"(v.z), "=f"(v.w) : "r"(a) : "memory"); return v; }
__device__ __forceinline__ void sts32(uint32_t a, uint32_t v) { asm volatile("st.shared.b32 [%0], %1;" ::"r"(a), "r"(v) : "memory"); }
__device__ __forceinline__ void sts64f(uint32_t a, float x, float y) { asm volatile("st.shared.v2.f32 [%0], {%1,%2};" ::"r"(a), "f"(x), "f"(y) : "memory"); }
__device__ __forceinline__ void sts128(uint32_t a, uint32_t x, uint32_t y, uint32_t z, uint32_t w) {
  asm volatile("st.shared.v4.b32 [%0], {%1,%2,%3,%4};" ::"r"(a), "r"(x), "r"(y), "r"(z), "r"(w) : "memory");
}
__device__ __forceinline__ void ldsm4(uint32_t (&r)[4], uint32_t a) {
  asm volatile("ldmatrix.sync.aligned.m8n8.x4.shared.b16 {%0,%1,%2,%3}, [%4];" : "=r"(r[0]), "=r"(r[1]), "=r"(r[2]), "=r"(r[3]) : "r"(a) : "memory");
}
__device__ __forceinline__ void stsm4t(uint32_t a, uint32_t r0, uint32_t r1, uint32_t r2, uint32_t r3) {
  asm volatile("stmatrix.sync.aligned.m8n8.x4.trans.shared.b16 [%0], {%1,%2,%3,%4};" ::"r"(a), "r"(r0), "r"(r1), "r"(r2), "r"(r3) : "memory");
}
__device__ __forceinline__ void stsm2t(uint32_t a, uint32_t r0, uint32_t r1) {
  asm volatile("stmatrix.sync.aligned.m8n8.x2.trans.shared.b16 [%0], {%1,%2};" ::"r"(a), "r"(r0), "r"(r1) : "memory");
}
__device__ __forceinline__ uint32_t pack_bf16(float lo, float hi) { uint32_t r; asm("cvt.rn.bf16x2.f32 %0, %1, %2;" : "=r"(r) : "f"(hi), "f"(lo)); return r; }
__device__ __forceinline__ float bf_lo(uint32_t v) { return __uint_as_float(v << 16); }
__device__ __forceinline__ float bf_hi(uint32_t v) { return __uint_as_float(v & 0xffff0000u); }
__device__ __forceinline__ uint32_t hfma2(uint32_t a, uint32_t b, uint32_t c) { uint32_t r; asm("fma.rn.bf16x2 %0, %1, %2, %3;" : "=r"(r) : "r"(a), "r"(b), "r"(c)); return r; }
__device__ __forceinline__ uint32_t hmul2(uint32_t a, uint32_t b) { uint32_t r; asm("mul.bf16x2 %0, %1, %2;" : "=r"(r) : "r"(a), "r"(b)); return r; }
__device__ __forceinline__ uint32_t hsub2(uint32_t a, uint32_t b) { uint32_t r; asm("sub.bf16x2 %0, %1, %2;" : "=r"(r) : "r"(a), "r"(b)); return r; }
__device__ __forceinline__ float gelu_tanh(float z) {
  float u = z * fmaf(z * z, 0.044715f * 0.7978845608028654f, 0.7978845608028654f);
  float t;
  asm("tanh.approx.f32 %0, %1;" : "=f"(t) : "f"(u));
  float hz = 0.5f * z;
  return fmaf(hz, t, hz);
}
__device__ __forceinline__ uint64_t mkdesc(uint32_t addr, uint32_t lbo, uint32_t sbo, uint32_t sw) {
  return (uint64_t)((addr & 0x3FFFF) >> 4) | ((uint64_t)(lbo >> 4) << 16) | ((uint64_t)(sbo >> 4) << 32) | ((uint64_t)sw << 62);
}
#define WG_FENCE() asm volatile("wgmma.fence.sync.aligned;" ::: "memory")
#define WG_COMMIT() asm volatile("wgmma.commit_group.sync.aligned;" ::: "memory")
#define WG_WAIT(n) asm volatile("wgmma.wait_group.sync.aligned %0;" ::"n"(n) : "memory")
template <int N> __device__ __forceinline__ void reg_fence(float (&d)[N]) {
#pragma unroll
  for (int i = 0; i < N; i++) asm volatile("" : "+f"(d[i])::"memory");
}

template<int TB> __device__ __forceinline__ void wg_ss80(float (&d)[40], uint64_t da, uint64_t db, int sd){
  asm volatile("{.reg .pred p; setp.ne.b32 p, %42, 0;\n"
   "wgmma.mma_async.sync.aligned.m64n80k16.f32.bf16.bf16 {%0,%1,%2,%3,%4,%5,%6,%7,%8,%9,%10,%11,%12,%13,%14,%15,%16,%17,%18,%19,%20,%21,%22,%23,%24,%25,%26,%27,%28,%29,%30,%31,%32,%33,%34,%35,%36,%37,%38,%39}, %40, %41, p, 1, 1, 1, %43;}"
   : "+f"(d[0]),"+f"(d[1]),"+f"(d[2]),"+f"(d[3]),"+f"(d[4]),"+f"(d[5]),"+f"(d[6]),"+f"(d[7]),"+f"(d[8]),"+f"(d[9]),"+f"(d[10]),"+f"(d[11]),"+f"(d[12]),"+f"(d[13]),"+f"(d[14]),"+f"(d[15]),"+f"(d[16]),"+f"(d[17]),"+f"(d[18]),"+f"(d[19]),"+f"(d[20]),"+f"(d[21]),"+f"(d[22]),"+f"(d[23]),"+f"(d[24]),"+f"(d[25]),"+f"(d[26]),"+f"(d[27]),"+f"(d[28]),"+f"(d[29]),"+f"(d[30]),"+f"(d[31]),"+f"(d[32]),"+f"(d[33]),"+f"(d[34]),"+f"(d[35]),"+f"(d[36]),"+f"(d[37]),"+f"(d[38]),"+f"(d[39])
   : "l"(da), "l"(db), "r"(sd), "n"(TB));
}
template<int TB> __device__ __forceinline__ void wg_ss152(float (&d)[76], uint64_t da, uint64_t db, int sd){
  asm volatile("{.reg .pred p; setp.ne.b32 p, %78, 0;\n"
   "wgmma.mma_async.sync.aligned.m64n152k16.f32.bf16.bf16 {%0,%1,%2,%3,%4,%5,%6,%7,%8,%9,%10,%11,%12,%13,%14,%15,%16,%17,%18,%19,%20,%21,%22,%23,%24,%25,%26,%27,%28,%29,%30,%31,%32,%33,%34,%35,%36,%37,%38,%39,%40,%41,%42,%43,%44,%45,%46,%47,%48,%49,%50,%51,%52,%53,%54,%55,%56,%57,%58,%59,%60,%61,%62,%63,%64,%65,%66,%67,%68,%69,%70,%71,%72,%73,%74,%75}, %76, %77, p, 1, 1, 1, %79;}"
   : "+f"(d[0]),"+f"(d[1]),"+f"(d[2]),"+f"(d[3]),"+f"(d[4]),"+f"(d[5]),"+f"(d[6]),"+f"(d[7]),"+f"(d[8]),"+f"(d[9]),"+f"(d[10]),"+f"(d[11]),"+f"(d[12]),"+f"(d[13]),"+f"(d[14]),"+f"(d[15]),"+f"(d[16]),"+f"(d[17]),"+f"(d[18]),"+f"(d[19]),"+f"(d[20]),"+f"(d[21]),"+f"(d[22]),"+f"(d[23]),"+f"(d[24]),"+f"(d[25]),"+f"(d[26]),"+f"(d[27]),"+f"(d[28]),"+f"(d[29]),"+f"(d[30]),"+f"(d[31]),"+f"(d[32]),"+f"(d[33]),"+f"(d[34]),"+f"(d[35]),"+f"(d[36]),"+f"(d[37]),"+f"(d[38]),"+f"(d[39]),"+f"(d[40]),"+f"(d[41]),"+f"(d[42]),"+f"(d[43]),"+f"(d[44]),"+f"(d[45]),"+f"(d[46]),"+f"(d[47]),"+f"(d[48]),"+f"(d[49]),"+f"(d[50]),"+f"(d[51]),"+f"(d[52]),"+f"(d[53]),"+f"(d[54]),"+f"(d[55]),"+f"(d[56]),"+f"(d[57]),"+f"(d[58]),"+f"(d[59]),"+f"(d[60]),"+f"(d[61]),"+f"(d[62]),"+f"(d[63]),"+f"(d[64]),"+f"(d[65]),"+f"(d[66]),"+f"(d[67]),"+f"(d[68]),"+f"(d[69]),"+f"(d[70]),"+f"(d[71]),"+f"(d[72]),"+f"(d[73]),"+f"(d[74]),"+f"(d[75])
   : "l"(da), "l"(db), "r"(sd), "n"(TB));
}
__device__ __forceinline__ void wg_rs64(float (&d)[32], const uint32_t (&a)[4], uint64_t db, int sd){
  asm volatile("{.reg .pred p; setp.ne.b32 p, %37, 0;\n"
   "wgmma.mma_async.sync.aligned.m64n64k16.f32.bf16.bf16 {%0,%1,%2,%3,%4,%5,%6,%7,%8,%9,%10,%11,%12,%13,%14,%15,%16,%17,%18,%19,%20,%21,%22,%23,%24,%25,%26,%27,%28,%29,%30,%31}, {%32,%33,%34,%35}, %36, p, 1, 1, 0;}"
   : "+f"(d[0]),"+f"(d[1]),"+f"(d[2]),"+f"(d[3]),"+f"(d[4]),"+f"(d[5]),"+f"(d[6]),"+f"(d[7]),"+f"(d[8]),"+f"(d[9]),"+f"(d[10]),"+f"(d[11]),"+f"(d[12]),"+f"(d[13]),"+f"(d[14]),"+f"(d[15]),"+f"(d[16]),"+f"(d[17]),"+f"(d[18]),"+f"(d[19]),"+f"(d[20]),"+f"(d[21]),"+f"(d[22]),"+f"(d[23]),"+f"(d[24]),"+f"(d[25]),"+f"(d[26]),"+f"(d[27]),"+f"(d[28]),"+f"(d[29]),"+f"(d[30]),"+f"(d[31])
   : "r"(a[0]),"r"(a[1]),"r"(a[2]),"r"(a[3]), "l"(db), "r"(sd));
}

template <int J> __device__ __forceinline__ void conv_issue(float (&d)[32], const uint32_t (&A)[16][4], uint64_t db) {
  WG_FENCE();
#pragma unroll
  for (int q = 0; q <= J; q++)
#pragma unroll
    for (int s = 0; s < 4; s++) wg_rs64(d, A[4 * q + s], db + ((1024 * (J - q) - 32 * s) >> 4), (q | s) != 0);
  WG_COMMIT();
}
template <int J>
__device__ __forceinline__ void conv_drain(float (&d)[32], float& c0, float& c1, uint32_t ex, uint32_t qc, uint32_t hst, int wg, int w, int lane) {
  reg_fence(d);
  const int g = lane >> 2, t = lane & 3;
  float z[8][2];
#pragma unroll
  for (int j = 0; j < 8; j++) {
    z[j][0] = d[4 * j] + c0;
    z[j][1] = d[4 * j + 1] + c1;
    if (j < 7) { c0 = d[4 * j + 2]; c1 = d[4 * j + 3]; }
    else { asm volatile("mov.b32 %0,%1;" : "=f"(c0) : "f"(d[4 * j + 2])); asm volatile("mov.b32 %0,%1;" : "=f"(c1) : "f"(d[4 * j + 3])); }
  }
  const uint32_t exl = ex + lane * 8;
#pragma unroll
  for (int pp = 1; pp < 4; pp++) {
    const bool later = (w + pp) >= 4;
    const int o = (w + pp) & 3;
    const int hi = later ? w : o, lo = later ? o : w;
    const uint32_t a = exl + (later ? 6144u : 0u) + (J & 1) * 3072u + (uint32_t)(hi * (hi - 1) / 2 + lo) * 512u;
    if (J < 3 || !later) {
      sts64f(a, z[2 * pp][0], z[2 * pp][1]);
      sts64f(a + 256, z[2 * pp + 1][0], z[2 * pp + 1][1]);
    }
  }
  bar_sync(1 + wg, 128);
#pragma unroll
  for (int pp = 1; pp < 4; pp++) {
    const int src = (w - pp) & 3;
    const bool later = src > w;
    const int hi = later ? src : w, lo = later ? w : src;
    const uint32_t a = exl + (later ? 6144u + ((J & 1) ^ 1) * 3072u : (J & 1) * 3072u) + (uint32_t)(hi * (hi - 1) / 2 + lo) * 512u;
    if (J > 0 || !later) {
      float2 u0 = lds64f(a), u1 = lds64f(a + 256);
      z[0][0] += u0.x; z[0][1] += u0.y; z[1][0] += u1.x; z[1][1] += u1.y;
    }
  }
  const int p = g & 1;
  const bool sw = t >= 2;
#pragma unroll
  for (int jj = 0; jj < 2; jj++) {
    float send = p ? z[jj][0] : z[jj][1], keep = p ? z[jj][1] : z[jj][0];
    float recv = __shfl_xor_sync(0xffffffffu, send, 4);
    float ylo = p ? recv : keep, yhi = p ? keep : recv;
    const uint32_t aq = qc + (8 * J + jj) * 256;
    uint32_t v0 = lds32(aq + (sw ? 32 : 0)), v1 = lds32(aq + (sw ? 0 : 32));
    uint32_t qv = sw ? v1 : v0, cv = sw ? v0 : v1;
    float hlo = fmaf(bf_lo(qv), ylo, bf_lo(cv)), hhi = fmaf(bf_hi(qv), yhi, bf_hi(cv));
    sts32(hst + (8 * J + jj) * 128, pack_bf16(hlo, hhi));
  }
}

struct Ring { uint32_t slot, ph; };
__device__ __forceinline__ void ring_adv(Ring& r, uint32_t step, uint32_t n) { r.slot += step; if (r.slot >= n) { r.slot -= n; r.ph ^= 1; } }

template <int N, int TBN, int NCH, int NX, uint32_t XB, int WSTEP, int XEB>
__device__ __forceinline__ void gemm_loop(float (&d)[N / 2], uint32_t sb, Ring& wr, Ring& xr, bool first_zero, bool release_x, bool lead) {
  const uint64_t da0 = mkdesc(sb + WR, 1024, 1024, 1);
  const uint64_t db0 = TBN ? mkdesc(sb + XR, 256, 1280, 3) : mkdesc(sb + XR, 16, 1024, 1);
  uint32_t pw = 0, px = 0;
  if (first_zero) {
#pragma unroll
    for (int i = 0; i < N / 2; i++) d[i] = 0.f;
  }
  reg_fence(d);
#pragma unroll 1
  for (int c = 0; c < NCH; c++) {
    mbar_wait(sb + BARS + 8 * (B_WF + wr.slot), wr.ph);
    mbar_wait(sb + BARS + 8 * (B_XF + xr.slot), xr.ph);
    const uint64_t da = da0 + wr.slot * (8192 >> 4), db = db0 + xr.slot * (XB >> 4);
    WG_FENCE();
#pragma unroll
    for (int k = 0; k < 4; k++) {
      const int sd = 1;
      if constexpr (N == 80) wg_ss80<TBN>(d, da + k * 128, db + k * (TBN ? 160 : 2), sd);
      else wg_ss152<TBN>(d, da + k * 128, db + k * 2, sd);
    }
    WG_COMMIT();
    if (c > 0) {
      WG_WAIT(1);
      if (lead) { mbar_arrive(pw); if (release_x) mbar_arrive(px); }
    }
    pw = sb + BARS + 8 * (B_WE + wr.slot);
    px = sb + BARS + 8 * (XEB + xr.slot);
    ring_adv(wr, WSTEP, NW);
    ring_adv(xr, 1, NX);
  }
  WG_WAIT(0);
  reg_fence(d);
  if (lead) { mbar_arrive(pw); if (release_x) mbar_arrive(px); }
}

__device__ __forceinline__ void colsum_job(const __nv_bfloat16* W, int ld, int rows, int c0, int nc, float* out, uint32_t sb, int tid) {
  const int ng = nc / 8;
  const int rs = 384 / ng;
  const int gi = tid % ng, ri = tid / ng;
  float a[8];
#pragma unroll
  for (int i = 0; i < 8; i++) a[i] = 0.f;
  if (ri < rs) {
#pragma unroll 8
    for (int r = ri; r < rows; r += rs) {
      uint4 v = __ldg(reinterpret_cast<const uint4*>(W + (size_t)r * ld + c0 + gi * 8));
      a[0] += bf_lo(v.x); a[1] += bf_hi(v.x); a[2] += bf_lo(v.y); a[3] += bf_hi(v.y);
      a[4] += bf_lo(v.z); a[5] += bf_hi(v.z); a[6] += bf_lo(v.w); a[7] += bf_hi(v.w);
    }
    const uint32_t s = sb + XR + (uint32_t)(ri * nc + gi * 8) * 4;
    sts128(s, __float_as_uint(a[0]), __float_as_uint(a[1]), __float_as_uint(a[2]), __float_as_uint(a[3]));
    sts128(s + 16, __float_as_uint(a[4]), __float_as_uint(a[5]), __float_as_uint(a[6]), __float_as_uint(a[7]));
  }
  bar_sync(7, 384);
  for (int c = tid; c < nc; c += 384) {
    float s = 0.f;
    for (int r = 0; r < rs; r++) s += __uint_as_float(lds32(sb + XR + (uint32_t)(r * nc + c) * 4));
    out[c0 + c] = s;
  }
  __threadfence();
  bar_sync(7, 384);
}

__global__ void __launch_bounds__(NTHR, 1) fused_kernel(const __grid_constant__ Params p) {
  extern __shared__ __align__(1024) uint8_t smem_raw[];
  const uint32_t sb = (uint32_t)__cvta_generic_to_shared(smem_raw);
  const int tid = threadIdx.x, lane = tid & 31;
  const int warp = __shfl_sync(0xffffffffu, tid >> 5, 0);
  const int wg = warp >> 2;
  const int b = blockIdx.x;
  const uint32_t bars = sb + BARS;
  if (warp == 13) {
    if (lane == 0) {
      if (sb & 1023) __trap();
      for (int i = 0; i < B_NUM; i++) {
        uint32_t cnt = 1;
        if (i == B_CONV) cnt = 3;
        if (i == B_XFREE) cnt = 3;
        if (i >= B_XE) cnt = 2;
        if (i >= B_X3E) cnt = 3;
        mbar_init(bars + 8 * i, cnt);
      }
      asm volatile("fence.mbarrier_init.release.cluster;" ::: "memory");
      if (b < 128) {
        mbar_expect(bars + 8 * B_KV, (b == 0 ? 32 : 35) * 1280);
        mbar_expect(bars + 8 * B_X, 16 * 1280);
      }
    }
    __syncwarp();
    if (b < 128) {
      for (int r = lane; r < 51; r += 32) {
        const __nv_bfloat16* src = r < 19 ? p.k + (size_t)(16 * b - 3 + r) * D_ : r < 35 ? p.v + (size_t)(16 * b + r - 19) * D_ : p.x + (size_t)(16 * b + r - 35) * D_;
        if (b > 0 || r >= 3) bulk_load(sb + PIN + r * PITCH, src, 1280, bars + 8 * (r < 35 ? B_KV : B_X));
      }
    }
  }
  __syncthreads();

  const int ti = b / 5, fj = b % 5;
  const int t3 = b / 9, f3 = b % 9;

  if (wg == 3) {
    asm volatile("setmaxnreg.dec.sync.aligned.u32 32;");
    if (warp == 12 && lane == 0 && b < 130) {
      if (b < 128) mbar_wait(bars + 8 * B_PRE, 0); else mbar_wait(bars + 8 * B_CS, 0);
      Ring r{0, 1};
      for (int ph = 0; ph < 4; ph++) {
        if (ph == 2 && b >= 126) continue;
        const CUtensorMap* tm = ph == 0 ? &p.w1 : ph == 1 ? &p.w2 : ph == 2 ? &p.w3 : &p.w4;
        const int nch = ph == 3 ? 27 : 10, nwg = ph == 2 ? 3 : 2, f0 = ph == 2 ? 192 * f3 : 128 * fj;
        for (int c = 0; c < nch; c++)
          for (int w = 0; w < nwg; w++) {
            mbar_wait(bars + 8 * (B_WE + r.slot), r.ph);
            mbar_expect(bars + 8 * (B_WF + r.slot), 8192);
            tma_load2(sb + WR + r.slot * 8192, tm, f0 + 64 * w, 64 * c, bars + 8 * (B_WF + r.slot));
            ring_adv(r, 1, NW);
          }
      }
    } else if (warp == 13 && lane == 0 && b < 130) {
      unsigned ep;
      asm volatile("ld.relaxed.gpu.global.u32 %0, [%1];" : "=r"(ep) : "l"(&g_epoch) : "memory");
      ep += 1;
      if (b < 128) {
        poll_flag(&g_flag[F_P * 32], ep * 128u);
        STAMP(20);
        for (int r = 0; r < 5; r++) {
          const int c = 128 * r + b;
          mbar_expect(bars + 8 * (B_U + r), 4096);
          bulk_load(sb + U_OFF + r * U_STRIDE + 128, g_kvT + (size_t)c * S_, 4096, bars + 8 * (B_U + r));
          mbar_expect(bars + 8 * (B_QC + r), 8192);
          bulk_load(sb + (r < 4 ? QC_OFF + r * 8192 : QC5), g_qc + (size_t)c * S_ * 2, 8192, bars + 8 * (B_QC + r));
        }
        mbar_wait(bars + 8 * B_CONV, 0);
      } else {
        mbar_wait(bars + 8 * B_CS, 0);
        if (ep != 0xffffffffu) flag_add(&g_flag[(F_C + 4) * 32]);
      }
      for (int c = 0; c < 10; c++) {
        if (!(c & 1)) poll_flag(&g_flag[(F_C + (c >> 1)) * 32], ep * (c == 8 ? 130u : 128u));
        mbar_expect(bars + 8 * (B_XF + c), 10240);
        bulk_load(sb + XR + c * 10240, g_hT + (size_t)ti * (D_ * TT) + c * 5120, 10240, bars + 8 * (B_XF + c));
      }
      STAMP(21);
      mbar_wait(bars + 8 * B_XFREE, 0);
      poll_flag(&g_flag[F_1 * 32], ep * 260u);
      STAMP(22);
      for (int c = 0; c < 10; c++) {
        mbar_expect(bars + 8 * (B_XF + c), 10240);
        tma_load2(sb + XR + c * 10240, &p.hsL, 64 * c, TT * ti, bars + 8 * (B_XF + c));
      }
      for (int c = 0; c < 10; c++) mbar_wait(bars + 8 * (B_XE + c), 0);
      if (b < 126) {
        poll_flag(&g_flag[F_2 * 32], ep * 260u);
        STAMP(23);
        for (int c = 0; c < 10; c++) {
          const int s = c % 5;
          if (c >= 5) mbar_wait(bars + 8 * (B_X3E + s), 0);
          mbar_expect(bars + 8 * (B_XF + s), 19456);
          tma_load2(sb + XR + s * 19456, &p.x1L, 64 * c, TT3 * t3, bars + 8 * (B_XF + s));
        }
        mbar_wait(bars + 8 * B_XFREE, 1);
      }
      poll_flag(&g_flag[F_3 * 32], ep * 378u);
      STAMP(24);
      {
        Ring r{0, 0};
        for (int c = 0; c < 27; c++) {
          if (c >= 10) mbar_wait(bars + 8 * (B_XE + r.slot), r.ph);
          mbar_expect(bars + 8 * (B_XF + r.slot), 10240);
          tma_load2(sb + XR + r.slot * 10240, &p.HL, 64 * c, TT * ti, bars + 8 * (B_XF + r.slot));
          ring_adv(r, 1, 10);
        }
      }
      if (b == 0) asm volatile("st.relaxed.gpu.global.u32 [%0], %1;" ::"l"(&g_epoch), "r"(ep) : "memory");
    } else if (warp == 14) {
      if (b < 128) {
        mbar_wait(bars + 8 * B_KV, 0);
        if (lane == 0) {
          l2_prefetch(reinterpret_cast<const uint8_t*>(p.pw1) + b * 6400, 6400);
          l2_prefetch(reinterpret_cast<const uint8_t*>(p.pw2) + b * 6400, 6400);
          l2_prefetch(reinterpret_cast<const uint8_t*>(p.pw3) + b * 17280, 17280);
          l2_prefetch(reinterpret_cast<const uint8_t*>(p.pw4) + b * 17280, 17280);
        }
      }
      if (b < 126) {
        unsigned ep;
        asm volatile("ld.relaxed.gpu.global.u32 %0, [%1];" : "=r"(ep) : "l"(&g_epoch) : "memory");
        ep += 1;
        mbar_wait(bars + 8 * B_XFREE, 0);
        if (lane == 0) poll_flag(&g_flag[F_S * 32], ep * 262u);
        __syncwarp();
        asm volatile("fence.acq_rel.gpu;" ::: "memory");
        for (int r = lane; r < TT3; r += 32) {
          const int tok = TT3 * t3 + r;
          float s = 0.f, ss = 0.f;
          if (tok < S_) {
            const float4* q = reinterpret_cast<const float4*>(g_st + (size_t)tok * 10);
#pragma unroll
            for (int i = 0; i < 5; i++) { float4 v = __ldcg(q + i); s += v.x + v.z; ss += v.y + v.w; }
          }
          const float m = s * (1.f / D_);
          const float var = fmaxf(ss * (1.f / D_) - m * m, 0.f);
          sts64f(sb + ST3 + r * 8, m, rsqrtf(var + EPS));
        }
        __syncwarp();
        if (lane == 0) mbar_arrive(bars + 8 * B_ST3);
      }
    }
  } else {
    asm volatile("setmaxnreg.inc.sync.aligned.u32 160;");
    const int w = warp & 3, g = lane >> 2, t = lane & 3;
    const bool lead = (tid & 127) == 0;
    if (b >= 128) {
      if (b < 130) colsum_job(p.pw1, D_, D_, (b - 128) * 320, 320, g_cs1, sb, tid);
      else colsum_job(p.pw3, F_, D_, (b - 130) * 864, 864, g_cs3, sb, tid);
      if (tid == 0) {
        if (b < 130) mbar_arrive(bars + 8 * B_CS); else flag_add(&g_flag[F_S * 32]);
      }
    } else {
      {
        uint4 fv[4]; uint32_t fp[4];
#pragma unroll
        for (int i = 0; i < 4; i++) {
          const int it = tid + 384 * i;
          if (it < 1280) {
            const __nv_bfloat16* src = p.ssm_k + (size_t)(128 * (it >> 8) + b) * S_ + 8 * (it & 255);
            fv[i] = __ldg(reinterpret_cast<const uint4*>(src));
            fp[i] = (it & 255) ? (uint32_t)__ldg(reinterpret_cast<const unsigned short*>(src) - 1) : 0u;
          }
        }
        uint32_t cw[4][2][5];
#pragma unroll
        for (int i = 0; i < 4; i++) {
          const int u = warp + 12 * i;
          if (u < 40) {
#pragma unroll
            for (int oc = 0; oc < 2; oc++) {
              const int ch = 16 * u + 8 * oc + 2 * t;
              uint4 v = __ldg(reinterpret_cast<const uint4*>(p.shift_k + 4 * ch));
              cw[i][oc][0] = __byte_perm(v.x, v.z, 0x5410); cw[i][oc][1] = __byte_perm(v.x, v.z, 0x7632);
              cw[i][oc][2] = __byte_perm(v.y, v.w, 0x5410); cw[i][oc][3] = __byte_perm(v.y, v.w, 0x7632);
              cw[i][oc][4] = __ldg(reinterpret_cast<const uint32_t*>(p.ssm_D + ch));
            }
          }
        }
        if (tid < 40) sts128(sb + U_OFF + (tid >> 3) * U_STRIDE + (tid & 7) * 16, 0, 0, 0, 0);
        else if (tid < 75) { const int i = tid - 40, r = i / 7, k = i % 7; sts32(sb + r * TAB_STRIDE + (k < 3 ? TAB_E + (1025 + k) * 4 : TAB_O + (1021 + k) * 4), 0); }
        if (b == 0 && tid < 240) sts128(sb + PIN + (tid / 80) * PITCH + (tid % 80) * 16, 0, 0, 0, 0);
#pragma unroll
        for (int i = 0; i < 4; i++) {
          const int it = tid + 384 * i;
          if (it < 1280) {
            const uint32_t tb = sb + (it >> 8) * TAB_STRIDE; const int s = it & 255;
            sts128(tb + TAB_O + (1020 - 4 * s) * 4, __byte_perm(fv[i].w, 0, 0x1032), __byte_perm(fv[i].z, 0, 0x1032), __byte_perm(fv[i].y, 0, 0x1032), __byte_perm(fv[i].x, 0, 0x1032));
            sts128(tb + TAB_E + (1021 - 4 * s) * 4, __byte_perm(fv[i].w, fv[i].z, 0x7610), __byte_perm(fv[i].z, fv[i].y, 0x7610), __byte_perm(fv[i].y, fv[i].x, 0x7610), __byte_perm(fv[i].x, fp[i], 0x5410));
          }
        }
        if (warp < 8) {
          mbar_wait(bars + 8 * B_X, 0);
          const int row = 2 * warp + (lane >> 4);
          float xv[40];
#pragma unroll
          for (int i = 0; i < 5; i++) {
            uint4 v = lds128(sb + PIN + (35 + row) * PITCH + ((lane & 15) + 16 * i) * 16);
            xv[8 * i] = bf_lo(v.x); xv[8 * i + 1] = bf_hi(v.x); xv[8 * i + 2] = bf_lo(v.y); xv[8 * i + 3] = bf_hi(v.y);
            xv[8 * i + 4] = bf_lo(v.z); xv[8 * i + 5] = bf_hi(v.z); xv[8 * i + 6] = bf_lo(v.w); xv[8 * i + 7] = bf_hi(v.w);
          }
          float s = 0.f;
#pragma unroll
          for (int i = 0; i < 40; i++) s += xv[i];
#pragma unroll
          for (int o = 8; o; o >>= 1) s += __shfl_xor_sync(0xffffffffu, s, o);
          const float m = s * (1.f / D_);
          float ss = 0.f;
#pragma unroll
          for (int i = 0; i < 40; i++) { const float dlt = xv[i] - m; ss = fmaf(dlt, dlt, ss); }
#pragma unroll
          for (int o = 8; o; o >>= 1) ss += __shfl_xor_sync(0xffffffffu, ss, o);
          if ((lane & 15) == 0) sts64f(sb + ROWST + row * 8, m, rsqrtf(ss * (1.f / D_) + EPS));
        }
        bar_sync(7, 384);
        mbar_wait(bars + 8 * B_X, 0);
        mbar_wait(bars + 8 * B_KV, 0);
        if (tid == 0) STAMP(1);
        const float2 st0 = lds64f(sb + ROWST + g * 8), st1 = lds64f(sb + ROWST + (8 + g) * 8);
        const int m_ = lane >> 3, rho = lane & 7;
        const uint32_t lrow = sb + PIN + ((m_ & 1) * 8 + rho) * PITCH + (m_ >> 1) * 16;
#pragma unroll
        for (int i = 0; i < 4; i++) {
          const int u = warp + 12 * i;
          if (u < 40) {
            uint32_t k0[4], k1[4], k2[4], k3[4], vv[4], xx[4];
            const uint32_t la = lrow + u * 32;
            ldsm4(k0, la + 3 * PITCH); ldsm4(k1, la + 2 * PITCH); ldsm4(k2, la + PITCH); ldsm4(k3, la);
            ldsm4(vv, la + 19 * PITCH); ldsm4(xx, la + 35 * PITCH);
            uint32_t kvr[4], qr[4], cr[4];
#pragma unroll
            for (int m = 0; m < 4; m++) {
              const int oc = m >> 1;
              uint32_t ks = hmul2(k3[m], cw[i][oc][3]);
              ks = hfma2(k2[m], cw[i][oc][2], ks);
              ks = hfma2(k1[m], cw[i][oc][1], ks);
              ks = hfma2(k0[m], cw[i][oc][0], ks);
              kvr[m] = hmul2(ks, vv[m]);
              const float mm = (m & 1) ? st1.x : st0.x, rr = (m & 1) ? st1.y : st0.y;
              const float xl = bf_lo(xx[m]), xh = bf_hi(xx[m]);
              const float ql = (xl - mm) * rr, qh = (xh - mm) * rr;
              qr[m] = pack_bf16(ql, qh);
              cr[m] = pack_bf16(fmaf(ql * bf_lo(cw[i][oc][4]), bf_lo(kvr[m]), xl), fmaf(qh * bf_hi(cw[i][oc][4]), bf_hi(kvr[m]), xh));
            }
            const int ch = 16 * u + 8 * (m_ >> 1) + rho, th = m_ & 1;
            stsm4t(sb + KVST + ch * 32 + ((th ^ ((ch >> 2) & 1)) << 4), kvr[0], kvr[1], kvr[2], kvr[3]);
            const uint32_t qa = sb + QCST + ch * 64; const int sx = (ch >> 1) & 3;
            stsm4t(qa + ((th ^ sx) << 4), qr[0], qr[1], qr[2], qr[3]);
            stsm4t(qa + (((2 + th) ^ sx) << 4), cr[0], cr[1], cr[2], cr[3]);
          }
        }
        fence_async_smem();
        bar_sync(7, 384);
        if (tid == 0) {
          mbar_arrive(bars + 8 * B_PRE);
          for (int r = 0; r < 5; r++) tma_store2(&p.kvT, 16 * b, 128 * r, sb + KVST + r * 4096);
          for (int r = 0; r < 5; r++) tma_store2(&p.qc, 32 * b, 128 * r, sb + QCST + r * 8192);
          store_commit_wait();
          flag_add(&g_flag[F_P * 32]);
          STAMP(2);
        }
      }
      {
        const uint32_t ex = sb + EXCH + wg * 12288;
        for (int r = wg; r < 5; r += 3) {
          const int L0 = 128 * w + 8 + g;
          const uint32_t ta = sb + r * TAB_STRIDE + ((g & 1) ? TAB_O + ((2047 - L0) / 2 + t) * 4 : TAB_E + ((2048 - L0) / 2 + t) * 4);
          const uint64_t db = mkdesc(sb + U_OFF + r * U_STRIDE + 128 - 16, 16, 128, 0);
          uint32_t A[16][4];
#pragma unroll
          for (int i = 0; i < 16; i++) {
            const uint32_t a = ta - (i >> 2) * 1024 - (i & 3) * 32;
            A[i][0] = lds32(a); A[i][1] = lds32(a - 128); A[i][2] = lds32(a + 16); A[i][3] = lds32(a - 112);
          }
          const uint32_t qc = sb + (r < 4 ? QC_OFF + r * 8192 : QC5) + w * 512 + t * 64 + (g & 1) * 16 + (g >> 1) * 4;
          const int ch = 128 * r + b;
          const uint32_t hst0 = sb + r * TAB_STRIDE;
          const uint32_t hst = hst0 + w * 256 + t * 32 + (((g & 1) ^ ((ch >> 2) & 1)) << 4) + (g >> 1) * 4;
          const int nxa = r == 0 ? 1 : r == 1 ? 0 : r == 2 ? 1 : r == 3 ? 2 : 0;
          const int nxb = r == 0 ? 2 : r == 1 ? 0 : 1;
          float d0[32], d1[32], c0 = 0.f, c1 = 0.f;
          mbar_wait(bars + 8 * (B_U + r), 0);
          if (r > 0) bar_sync(4 + wg, 256);
          conv_issue<0>(d0, A, db);
          conv_issue<1>(d1, A, db);
          bar_arrive(4 + nxa, 256);
          mbar_wait(bars + 8 * (B_QC + r), 0);
          WG_WAIT(1);
          conv_drain<0>(d0, c0, c1, ex, qc, hst, wg, w, lane);
          if (tid % 128 < 16) sts32(hst0 + 4096 + (tid & 15) * 4, 0);
          WG_WAIT(0);
          conv_drain<1>(d1, c0, c1, ex, qc, hst, wg, w, lane);
          bar_sync(4 + wg, 256);
          conv_issue<2>(d0, A, db);
          conv_issue<3>(d1, A, db);
          if (r < 4) bar_arrive(4 + nxb, 256);
          WG_WAIT(1);
          conv_drain<2>(d0, c0, c1, ex, qc, hst, wg, w, lane);
          WG_WAIT(0);
          conv_drain<3>(d1, c0, c1, ex, qc, hst, wg, w, lane);
          fence_async_smem();
          bar_sync(1 + wg, 128);
          if (lead) {
            tma_store5(&p.hT, 0, ch & 7, 0, ch >> 3, 0, hst0);
            store_commit_wait();
            flag_add(&g_flag[(F_C + r) * 32]);
            STAMP(3 + r);
          }
        }
        if (lead) mbar_arrive(bars + 8 * B_CONV);
      }
    }
    if (b < 130) {
      Ring wr{(uint32_t)wg, 0}, xr{0, 0};
      uint32_t res[20];
      const int f0 = 128 * fj + 64 * wg + 16 * w + g;
      const int m_ = lane >> 3, rho = lane & 7;
      if (wg == 2) {
        const int lt = tid - 256;
        float s[8], ss[8];
#pragma unroll
        for (int i = 0; i < 8; i++) { s[i] = 0.f; ss[i] = 0.f; }
        if (w < 3) {
          const bool act = lt < 80;
          for (int c = 0; c < 10; c++) {
            mbar_wait(bars + 8 * (B_XF + c), 0);
            if (act) {
#pragma unroll
              for (int k1 = 0; k1 < 8; k1++) {
                uint4 v = lds128(sb + XR + c * 10240 + k1 * 1280 + lt * 16);
                float f;
                f = bf_lo(v.x); s[0] += f; ss[0] = fmaf(f, f, ss[0]); f = bf_hi(v.x); s[1] += f; ss[1] = fmaf(f, f, ss[1]);
                f = bf_lo(v.y); s[2] += f; ss[2] = fmaf(f, f, ss[2]); f = bf_hi(v.y); s[3] += f; ss[3] = fmaf(f, f, ss[3]);
                f = bf_lo(v.z); s[4] += f; ss[4] = fmaf(f, f, ss[4]); f = bf_hi(v.z); s[5] += f; ss[5] = fmaf(f, f, ss[5]);
                f = bf_lo(v.w); s[6] += f; ss[6] = fmaf(f, f, ss[6]); f = bf_hi(v.w); s[7] += f; ss[7] = fmaf(f, f, ss[7]);
              }
            }
          }
#pragma unroll
          for (int i = 0; i < 8; i++) {
            s[i] += __shfl_xor_sync(0xffffffffu, s[i], 2); ss[i] += __shfl_xor_sync(0xffffffffu, ss[i], 2);
            s[i] += __shfl_xor_sync(0xffffffffu, s[i], 4); ss[i] += __shfl_xor_sync(0xffffffffu, ss[i], 4);
            s[i] += __shfl_xor_sync(0xffffffffu, s[i], 9); ss[i] += __shfl_xor_sync(0xffffffffu, ss[i], 9);
          }
          const int k0 = (lt >> 1) & 7, half = (lt & 1) ^ (k0 >> 2);
          float sv = s[0], sq = ss[0];
#pragma unroll
          for (int i = 1; i < 8; i++) if (k0 == i) { sv = s[i]; sq = ss[i]; }
          if (act) {
            const float m = sv * (1.f / D_);
            const float var = fmaxf(sq * (1.f / D_) - m * m, 0.f);
            const float r2 = rsqrtf(var + EPS);
            const float r3 = rsqrtf(var * r2 * r2 + EPS);
            const int tok = (lt >> 4) * 16 + half * 8 + k0;
            sts128(sb + TOKST + tok * 16, __float_as_uint(m), __float_as_uint(r2), __float_as_uint(r2 * r3), 0);
          }
        }
        bar_sync(3, 128);
        if (lead) { mbar_arrive(bars + 8 * B_TOK); mbar_arrive(bars + 8 * B_XFREE); }
        mbar_wait(bars + 8 * (B_XE + 9), 0);
        wr.slot = (40 + 2) % NW; wr.ph = ((40 + 2) / NW) & 1;
      } else {
        float d[40];
        gemm_loop<80, 1, 10, 10, 10240, 2, B_XE>(d, sb, wr, xr, true, false, lead);
        if (lead) STAMP(8 + wg);
        const float cs0 = __ldcg(g_cs1 + f0), cs1 = __ldcg(g_cs1 + f0 + 8);
#pragma unroll
        for (int j = 0; j < 10; j++) {
          const uint32_t a = sb + XR + (f0 >> 3) * 1280 + (j >> 1) * 256 + g * 32 + (((j & 1) ^ (g >> 2)) << 4) + t * 4;
          res[2 * j] = lds32(a); res[2 * j + 1] = lds32(a + 1280);
        }
        mbar_wait(bars + 8 * B_TOK, 0);
        bar_sync(1 + wg, 128);
        if (lead) mbar_arrive(bars + 8 * B_XFREE);
        const uint32_t stg = sb + GST + wg * 10240;
        {
          uint32_t pk[20];
#pragma unroll
          for (int j = 0; j < 10; j++) {
            const float4 sa = lds128f(sb + TOKST + (8 * j + 2 * t) * 16), sc = lds128f(sb + TOKST + (8 * j + 2 * t + 1) * 16);
            pk[2 * j] = pack_bf16(gelu_tanh(sa.z * fmaf(-sa.x, cs0, d[4 * j])), gelu_tanh(sc.z * fmaf(-sc.x, cs0, d[4 * j + 1])));
            pk[2 * j + 1] = pack_bf16(gelu_tanh(sa.z * fmaf(-sa.x, cs1, d[4 * j + 2])), gelu_tanh(sc.z * fmaf(-sc.x, cs1, d[4 * j + 3])));
            d[4 * j] = (bf_lo(res[2 * j]) - sa.x) * sa.y; d[4 * j + 1] = (bf_hi(res[2 * j]) - sc.x) * sc.y;
            d[4 * j + 2] = (bf_lo(res[2 * j + 1]) - sa.x) * sa.y; d[4 * j + 3] = (bf_hi(res[2 * j + 1]) - sc.x) * sc.y;
          }
#pragma unroll
          for (int j = 0; j < 10; j += 2) {
            const int tok = 8 * (j + (m_ >> 1)) + rho, chunk = 2 * (w & 1) + (m_ & 1);
            stsm4t(stg + (w >> 1) * 5120 + tok * 64 + ((chunk ^ ((tok >> 1) & 3)) << 4), pk[2 * j], pk[2 * j + 1], pk[2 * j + 2], pk[2 * j + 3]);
          }
        }
        fence_async_smem();
        bar_sync(1 + wg, 128);
        if (lead) {
#pragma unroll
          for (int hf = 0; hf < 2; hf++) {
            const int f = 128 * fj + 64 * wg + 32 * hf, grp = f / 160;
            const int sh = grp == 0 ? 1 : grp == 1 ? -1 : grp == 2 ? 2 : -2;
            tma_store2(&p.hsS, f, TT * ti + 2 + sh, stg + hf * 5120);
          }
          store_commit_wait();
          flag_add(&g_flag[F_1 * 32]);
          STAMP(10 + wg);
        }
        gemm_loop<80, 0, 10, 10, 10240, 2, B_XE>(d, sb, wr, xr, false, true, lead);
        if (lead) STAMP(12 + wg);
        bar_sync(1 + wg, 128);
        {
          uint32_t pk[20];
#pragma unroll
          for (int j = 0; j < 20; j++) {
            pk[j] = pack_bf16(d[2 * j], d[2 * j + 1]);
            res[j] = pack_bf16(bf_lo(res[j]) + bf_lo(pk[j]), bf_hi(res[j]) + bf_hi(pk[j]));
          }
#pragma unroll
          for (int j = 0; j < 10; j += 2) {
            const int tok = 8 * (j + (m_ >> 1)) + rho, chunk = 2 * w + (m_ & 1);
            stsm4t(stg + tok * 128 + ((chunk ^ (tok & 7)) << 4), pk[2 * j], pk[2 * j + 1], pk[2 * j + 2], pk[2 * j + 3]);
          }
        }
        fence_async_smem();
        bar_sync(1 + wg, 128);
        if (lead) {
          tma_store2(&p.x1S, 128 * fj + 64 * wg, TT * ti, stg);
          store_commit_wait();
          flag_add(&g_flag[F_2 * 32]);
          STAMP(14 + wg);
        }
        {
          const int lt = tid & 127, tok = TT * ti + lt;
          if (lt < 80) {
            float s = 0.f, ss = 0.f;
#pragma unroll
            for (int i = 0; i < 8; i++) {
              uint4 v = lds128(stg + lt * 128 + (((i + lt) & 7) << 4));
              float f;
              f = bf_lo(v.x); s += f; ss = fmaf(f, f, ss); f = bf_hi(v.x); s += f; ss = fmaf(f, f, ss);
              f = bf_lo(v.y); s += f; ss = fmaf(f, f, ss); f = bf_hi(v.y); s += f; ss = fmaf(f, f, ss);
              f = bf_lo(v.z); s += f; ss = fmaf(f, f, ss); f = bf_hi(v.z); s += f; ss = fmaf(f, f, ss);
              f = bf_lo(v.w); s += f; ss = fmaf(f, f, ss); f = bf_hi(v.w); s += f; ss = fmaf(f, f, ss);
            }
            if (tok < S_) g_st[(size_t)tok * 10 + 2 * fj + wg] = make_float2(s, ss);
            __threadfence();
          }
          bar_sync(1 + wg, 128);
          if (lead) flag_add(&g_flag[F_S * 32]);
        }
        wr.slot = (40 + wg) % NW; wr.ph = ((40 + wg) / NW) & 1;
      }
      if (b < 126) {
        float d[76];
        Ring x3{0, 0};
        gemm_loop<152, 0, 10, 5, 19456, 3, B_X3E>(d, sb, wr, x3, true, true, lead);
        if (lead) STAMP(16 + wg);
        const int f = 192 * f3 + 64 * wg + 16 * w + g;
        mbar_wait(bars + 8 * B_ST3, 0);
        const float cs0 = __ldcg(g_cs3 + f), cs1 = __ldcg(g_cs3 + f + 8);
        bar_sync(7, 384);
        const uint32_t stg = sb + XR + wg * 19456;
#pragma unroll
        for (int j = 0; j < 19; j += 2) {
          uint32_t pk[4];
#pragma unroll
          for (int jj = 0; jj < 2; jj++) {
            if (j + jj < 19) {
              const float4 sa = lds128f(sb + ST3 + (8 * (j + jj) + 2 * t) * 8);
              const int o = 4 * (j + jj);
              pk[2 * jj] = pack_bf16(gelu_tanh(sa.y * fmaf(-sa.x, cs0, d[o])), gelu_tanh(sa.w * fmaf(-sa.z, cs0, d[o + 1])));
              pk[2 * jj + 1] = pack_bf16(gelu_tanh(sa.y * fmaf(-sa.x, cs1, d[o + 2])), gelu_tanh(sa.w * fmaf(-sa.z, cs1, d[o + 3])));
            }
          }
          const int tok = 8 * (j + (m_ >> 1)) + rho, chunk = 2 * w + (m_ & 1);
          const uint32_t a = stg + tok * 128 + ((chunk ^ (tok & 7)) << 4);
          if (j + 1 < 19) stsm4t(a, pk[0], pk[1], pk[2], pk[3]); else stsm2t(a, pk[0], pk[1]);
        }
        fence_async_smem();
        bar_sync(1 + wg, 128);
        if (lead) {
          tma_store2(&p.HS, 192 * f3 + 64 * wg, TT3 * t3, stg);
          store_commit_wait();
          flag_add(&g_flag[F_3 * 32]);
          mbar_arrive(bars + 8 * B_XFREE);
          STAMP(25 + wg);
        }
      }
      if (wg < 2) {
        const int base = b < 126 ? 70 : 40;
        wr.slot = (base + wg) % NW; wr.ph = ((base + wg) / NW) & 1;
        xr.slot = 0; xr.ph = 0;
        float d[40];
#pragma unroll
        for (int j = 0; j < 20; j++) { d[2 * j] = bf_lo(res[j]); d[2 * j + 1] = bf_hi(res[j]); }
        gemm_loop<80, 0, 27, 10, 10240, 2, B_XE>(d, sb, wr, xr, false, true, lead);
        if (lead) STAMP(28 + wg);
        const uint32_t stg = sb + GST + wg * 10240;
#pragma unroll
        for (int j = 0; j < 10; j += 2) {
          const int tok = 8 * (j + (m_ >> 1)) + rho, chunk = 2 * w + (m_ & 1);
          stsm4t(stg + tok * 128 + ((chunk ^ (tok & 7)) << 4), pack_bf16(d[4 * j], d[4 * j + 1]), pack_bf16(d[4 * j + 2], d[4 * j + 3]),
                 pack_bf16(d[4 * j + 4], d[4 * j + 5]), pack_bf16(d[4 * j + 6], d[4 * j + 7]));
        }
        fence_async_smem();
        bar_sync(1 + wg, 128);
        if (lead) {
          tma_store2(&p.outS, 128 * fj + 64 * wg, TT * ti, stg);
          store_commit_wait();
          STAMP(30 + wg);
        }
      }
    }
  }
}

typedef CUresult (*EncFn)(CUtensorMap*, CUtensorMapDataType, cuuint32_t, void*, const cuuint64_t*, const cuuint64_t*, const cuuint32_t*,
                          const cuuint32_t*, CUtensorMapInterleave, CUtensorMapSwizzle, CUtensorMapL2promotion, CUtensorMapFloatOOBfill);

void make2d(EncFn enc, CUtensorMap* tm, const void* ptr, uint64_t inner, uint64_t outer, uint32_t bi, uint32_t bo, CUtensorMapSwizzle sw) {
  cuuint64_t gd[2] = {inner, outer};
  cuuint64_t gs[1] = {inner * 2};
  cuuint32_t bd[2] = {bi, bo}, es[2] = {1, 1};
  CUresult rr = enc(tm, CU_TENSOR_MAP_DATA_TYPE_BFLOAT16, 2, const_cast<void*>(ptr), gd, gs, bd, es, CU_TENSOR_MAP_INTERLEAVE_NONE, sw,
      CU_TENSOR_MAP_L2_PROMOTION_L2_128B, CU_TENSOR_MAP_FLOAT_OOB_FILL_NONE);
  (void)rr;
}

}

extern "C" void kernel_launch(void* const* d_in, const int* in_sizes, int n_in, void* d_out, int out_size) {
  (void)in_sizes; (void)n_in; (void)out_size;
  static EncFn enc = nullptr;
  static void *kvT, *qc, *hT, *hs, *x1, *H;
  if (!enc) {
    void* fn = nullptr;
    cudaDriverEntryPointQueryResult qr;
    cudaGetDriverEntryPoint("cuTensorMapEncodeTiled", &fn, cudaEnableDefault, &qr);
    enc = (EncFn)fn;
    cudaFuncSetAttribute(fused_kernel, cudaFuncAttributeMaxDynamicSharedMemorySize, SMEM_BYTES);
    cudaGetSymbolAddress(&kvT, g_kvT); cudaGetSymbolAddress(&qc, g_qc); cudaGetSymbolAddress(&hT, g_hT);
    cudaGetSymbolAddress(&hs, g_hs); cudaGetSymbolAddress(&x1, g_x1); cudaGetSymbolAddress(&H, g_H);
  }
  Params p;
  p.x = (const __nv_bfloat16*)d_in[0]; p.k = (const __nv_bfloat16*)d_in[1]; p.v = (const __nv_bfloat16*)d_in[2];
  p.shift_k = (const __nv_bfloat16*)d_in[3]; p.ssm_k = (const __nv_bfloat16*)d_in[4]; p.ssm_D = (const __nv_bfloat16*)d_in[5];
  p.pw1 = (const __nv_bfloat16*)d_in[7]; p.pw2 = (const __nv_bfloat16*)d_in[8]; p.pw3 = (const __nv_bfloat16*)d_in[9]; p.pw4 = (const __nv_bfloat16*)d_in[10];
  make2d(enc, &p.w1, p.pw1, D_, D_, 64, 64, CU_TENSOR_MAP_SWIZZLE_128B);
  make2d(enc, &p.w2, p.pw2, D_, D_, 64, 64, CU_TENSOR_MAP_SWIZZLE_128B);
  make2d(enc, &p.w3, p.pw3, F_, D_, 64, 64, CU_TENSOR_MAP_SWIZZLE_128B);
  make2d(enc, &p.w4, p.pw4, D_, F_, 64, 64, CU_TENSOR_MAP_SWIZZLE_128B);
  make2d(enc, &p.kvT, kvT, S_, D_, 16, 128, CU_TENSOR_MAP_SWIZZLE_32B);
  make2d(enc, &p.qc, qc, 2 * S_, D_, 32, 128, CU_TENSOR_MAP_SWIZZLE_64B);
  {
    cuuint64_t gd[5] = {16, 8, 5, 80, 26};
    cuuint64_t gs[4] = {32, 256, 1280, 102400};
    cuuint32_t bd[5] = {16, 1, 5, 1, 26}, es[5] = {1, 1, 1, 1, 1};
    CUresult rr = enc(&p.hT, CU_TENSOR_MAP_DATA_TYPE_BFLOAT16, 5, hT, gd, gs, bd, es, CU_TENSOR_MAP_INTERLEAVE_NONE, CU_TENSOR_MAP_SWIZZLE_NONE,
        CU_TENSOR_MAP_L2_PROMOTION_NONE, CU_TENSOR_MAP_FLOAT_OOB_FILL_NONE);
    (void)rr;
  }
  make2d(enc, &p.hsS, hs, D_, S_ + 2, 32, TT, CU_TENSOR_MAP_SWIZZLE_64B);
  make2d(enc, &p.hsL, (__nv_bfloat16*)hs + 2 * D_, D_, S_, 64, TT, CU_TENSOR_MAP_SWIZZLE_128B);
  make2d(enc, &p.x1S, x1, D_, S_, 64, TT, CU_TENSOR_MAP_SWIZZLE_128B);
  make2d(enc, &p.x1L, x1, D_, S_, 64, TT3, CU_TENSOR_MAP_SWIZZLE_128B);
  make2d(enc, &p.HS, H, F_, S_, 64, TT3, CU_TENSOR_MAP_SWIZZLE_128B);
  make2d(enc, &p.HL, H, F_, S_, 64, TT, CU_TENSOR_MAP_SWIZZLE_128B);
  make2d(enc, &p.outS, d_out, D_, S_, 64, TT, CU_TENSOR_MAP_SWIZZLE_128B);
  fused_kernel<<<NCTA, NTHR, SMEM_BYTES, cudaStreamPerThread>>>(p);
}
```

```cpp
#include <cuda_runtime.h>
#include <cuda_bf16.h>
#include <cuda.h>
#include <stdint.h>

namespace {

constexpr int S_ = 2048, D_ = 640, F_ = 1728;
constexpr int NCTA = 132;
constexpr int NTHR = 512;
constexpr int TT = 80;
constexpr int TT3 = 151;
constexpr float EPS = 1e-5f;
#define DEFER_F 1
#define CORDER 1
#define PIPE_LATE 1
#define GLOBAL_F1 0
#define GLOBAL_F2 0
#define STATS_LATE 1
#define BATCH3 0
#define SPACK 1
#define AEARLY 0
#define AL1 0
#define AL2 0
#define AL3 0
#define MAP3 1
#define TMPF 1
#define GLOBAL_F3 1

constexpr uint32_t XR = 0;
constexpr uint32_t WR = 102400;
constexpr uint32_t CR = 176128;
constexpr uint32_t TAB_E = 3 * 4, TAB_O = 1044 * 4;
__host__ __device__ constexpr uint32_t QCB(int r) { return r < 4 ? 20992 * r : CR + 36864; }
__host__ __device__ constexpr uint32_t TABB(int r) { return 20992 * r + (r < 4 ? 8192 : 0); }
__host__ __device__ constexpr uint32_t UB(int r) { return TABB(r) + 8320; }
constexpr uint32_t PK = WR;
constexpr uint32_t PX = WR + 5 * 9216;
constexpr uint32_t PSK = PX + 20480;
constexpr uint32_t EXCH = CR;
constexpr uint32_t GST = CR;
constexpr uint32_t STRAW = CR + 29696;
constexpr uint32_t MISC = CR + 45056;
constexpr uint32_t BARS = MISC;
constexpr uint32_t ROWST = MISC + 4096;
constexpr uint32_t TOKST = MISC + 1024;
constexpr uint32_t CS1S = MISC + 2304;
constexpr uint32_t ST3 = MISC + 2816;
constexpr uint32_t XST = MISC + 4864;
constexpr uint32_t SMEM_BYTES = 232448;
enum { B_X = 0, B_KV = 1  , B_F = 6  , B_U = 11  , B_QC = 16  , B_TAB = 21  , B_PST = 26  ,
       B_HST = 31  , B_HDONE = 36  , B_ONES = 41, B_CS, B_TOK, B_ST3, B_XFREE, B_PDONE,
       B_SG = 47  , B_SD = 50  , B_SS = 53  ,
       B_WF1 = 55  , B_WE1 = 64  , B_WF2 = 73  , B_WE2 = 77  , B_WF3 = 81  , B_WE3 = 84  ,
       B_XF = 87  , B_XE = 97  , B_X3E = 107  , B_WF4 = 112  , B_WE4 = 118  , B_STRAW = 124, B_NUM = 125 };
enum { F_P = 0  , F_C = 5  , F_1 = 10  , F_2 = 36  , F_S = 88  , F_3 = 114  , F_NUM = 156 };

struct Params {
  CUtensorMap w1p, w2d, w3t, w3, w4p, kvT, qc, hT, hsS, hsL, x1S, x1L, HS, HL, outS, kin, vin, xin, stL;
  const __nv_bfloat16 *shift_k, *ssm_k, *ssm_D, *pw1, *pw2, *pw3, *pw4;
};

}

__device__ __align__(1024) __nv_bfloat16 g_kvT[D_ * S_];
__device__ __align__(1024) __nv_bfloat16 g_qc[D_ * S_ * 2];
__device__ __align__(1024) __nv_bfloat16 g_hT[26 * D_ * TT];
__device__ __align__(1024) __nv_bfloat16 g_hs[(S_ + 2) * D_];
__device__ __align__(1024) __nv_bfloat16 g_x1[S_ * D_];
__device__ __align__(1024) __nv_bfloat16 g_H[S_ * F_];
__device__ __align__(1024) float2 g_st[10 * 2176];
__device__ __align__(1024) float g_cs1[4 * D_];
__device__ __align__(1024) unsigned g_flag[F_NUM * 32];
__device__ unsigned g_epoch;
#define STAMP(i) do {} while (0)
#define STAMPV(i, v) do {} while (0)
#define PROF_END() do {} while (0)
#define PROF_ARG
#define PROF_PASS

namespace {

__device__ __forceinline__ void mbar_init(uint32_t b, uint32_t c) { asm volatile("mbarrier.init.shared::cta.b64 [%0], %1;" ::"r"(b), "r"(c)); }
__device__ __forceinline__ void mbar_expect(uint32_t b, uint32_t bytes) {
  asm volatile("mbarrier.arrive.expect_tx.shared::cta.b64 _, [%0], %1;" ::"r"(b), "r"(bytes) : "memory");
}
__device__ __forceinline__ void mbar_arrive(uint32_t b) { asm volatile("mbarrier.arrive.shared::cta.b64 _, [%0];" ::"r"(b) : "memory"); }
__device__ __forceinline__ void mbar_wait(uint32_t b, uint32_t par) {
  uint32_t ok;
  asm volatile(
      "{.reg .pred p; .reg .u32 c; mov.u32 c, 0;\n"
      "WL: mbarrier.try_wait.parity.shared::cta.b64 p, [%1], %2;\n"
      "@p bra WD;\n"
      "add.u32 c, c, 1; setp.lt.u32 p, c, 4000000; @p bra WL; trap;\n"
      "WD: mov.u32 %0, 1;}"
      : "=r"(ok) : "r"(b), "r"(par) : "memory");
}
__device__ __forceinline__ void mbar_wait2(uint32_t b0, uint32_t p0, uint32_t b1, uint32_t p1) {
  asm volatile(
      "{.reg .pred p, q; .reg .u32 c; mov.u32 c, 0;\n"
      "WL: mbarrier.try_wait.parity.shared::cta.b64 p, [%0], %1;\n"
      "mbarrier.try_wait.parity.shared::cta.b64 q, [%2], %3;\n"
      "and.pred p, p, q;\n"
      "@p bra WD;\n"
      "add.u32 c, c, 1; setp.lt.u32 p, c, 4000000; @p bra WL; trap;\n"
      "WD: }" ::"r"(b0), "r"(p0), "r"(b1), "r"(p1) : "memory");
}
__device__ __forceinline__ void poll3(const unsigned* f0, const unsigned* f1, const unsigned* f2, unsigned target) {
  asm volatile(
      "{.reg .pred p; .reg .u32 a, b, c, n; mov.u32 n, 0;\n"
      "PL: ld.relaxed.gpu.global.u32 a, [%0]; ld.relaxed.gpu.global.u32 b, [%1]; ld.relaxed.gpu.global.u32 c, [%2];\n"
      "sub.u32 a, a, %3; sub.u32 b, b, %3; sub.u32 c, c, %3; or.b32 a, a, b; or.b32 a, a, c; setp.ge.s32 p, a, 0;\n"
      "@p bra.uni PD;\n"
      "add.u32 n, n, 1; setp.lt.u32 p, n, 4000000; @p bra.uni PL; trap;\n"
      "PD: }" ::"l"(f0), "l"(f1), "l"(f2), "r"(target) : "memory");
}
__device__ __forceinline__ void poll1(const unsigned* f, unsigned target) {
  asm volatile(
      "{.reg .pred p; .reg .u32 a, n; mov.u32 n, 0;\n"
      "PL: ld.relaxed.gpu.global.u32 a, [%0]; sub.u32 a, a, %1; setp.ge.s32 p, a, 0;\n"
      "@p bra.uni PD;\n"
      "add.u32 n, n, 1; setp.lt.u32 p, n, 4000000; @p bra.uni PL; trap;\n"
      "PD: }" ::"l"(f), "r"(target) : "memory");
}
__device__ __forceinline__ void align_time(uint32_t mask) {
  if (mask)
    asm volatile("{.reg .pred p; .reg .u32 t, s; mov.u32 s, %%globaltimer_lo; or.b32 s, s, %0;\n"
                 "AL: mov.u32 t, %%globaltimer_lo; sub.u32 t, s, t; setp.ge.s32 p, t, 0; @p bra.uni AL;}" ::"r"(mask));
}
__device__ __forceinline__ bool elect() {
  uint32_t p;
  asm volatile("{.reg .pred q; elect.sync _|q, 0xffffffff; selp.u32 %0,1,0,q;}" : "=r"(p));
  return p;
}
__device__ __forceinline__ void flag_add(unsigned* f) { asm volatile("red.relaxed.gpu.global.add.u32 [%0], 1;" ::"l"(f) : "memory"); }
__device__ __forceinline__ void tma_load3(uint32_t dst, const CUtensorMap* tm, int c0, int c1, int c2, uint32_t bar) {
  asm volatile("cp.async.bulk.tensor.3d.shared::cluster.global.mbarrier::complete_tx::bytes [%0], [%1, {%3,%4,%5}], [%2];" ::"r"(dst), "l"(tm), "r"(bar), "r"(c0), "r"(c1), "r"(c2) : "memory");
}
__device__ __forceinline__ void tma_prefetch3(const CUtensorMap* tm, int c0, int c1, int c2) {
  asm volatile("cp.async.bulk.prefetch.tensor.3d.L2.global.tile [%0, {%1,%2,%3}];" ::"l"(tm), "r"(c0), "r"(c1), "r"(c2) : "memory");
}
__device__ __forceinline__ void bulk_store(void* dst, uint32_t src, uint32_t bytes) {
  asm volatile("cp.async.bulk.global.shared::cta.bulk_group [%0], [%1], %2;" ::"l"(dst), "r"(src), "r"(bytes) : "memory");
}
__device__ __forceinline__ uint32_t swz128(uint32_t a) { return a ^ ((a >> 3) & 0x70u); }
__device__ __forceinline__ void bulk_load(uint32_t dst, const void* src, uint32_t bytes, uint32_t bar) {
  asm volatile("cp.async.bulk.shared::cluster.global.mbarrier::complete_tx::bytes [%0], [%1], %2, [%3];" ::"r"(dst), "l"(src), "r"(bytes), "r"(bar) : "memory");
}
__device__ __forceinline__ void tma_load2(uint32_t dst, const CUtensorMap* tm, int c0, int c1, uint32_t bar) {
  asm volatile("cp.async.bulk.tensor.2d.shared::cluster.global.mbarrier::complete_tx::bytes [%0], [%1, {%3,%4}], [%2];" ::"r"(dst), "l"(tm), "r"(bar), "r"(c0), "r"(c1) : "memory");
}
__device__ __forceinline__ void tma_store2(const CUtensorMap* tm, int c0, int c1, uint32_t src) {
  asm volatile("cp.async.bulk.tensor.2d.global.shared::cta.bulk_group [%0, {%2,%3}], [%1];" ::"l"(tm), "r"(src), "r"(c0), "r"(c1) : "memory");
}
__device__ __forceinline__ void tma_store5(const CUtensorMap* tm, int c0, int c1, int c2, int c3, int c4, uint32_t src) {
  asm volatile("cp.async.bulk.tensor.5d.global.shared::cta.bulk_group [%0, {%2,%3,%4,%5,%6}], [%1];" ::"l"(tm), "r"(src), "r"(c0), "r"(c1), "r"(c2), "r"(c3), "r"(c4) : "memory");
}
__device__ __forceinline__ void store_commit_wait() {
  asm volatile("cp.async.bulk.commit_group;" ::: "memory");
  asm volatile("cp.async.bulk.wait_group 0;" ::: "memory");
}
__device__ __forceinline__ void flag_release(unsigned* f) {
  asm volatile("fence.acq_rel.gpu;" ::: "memory");
  flag_add(f);
}
__device__ __forceinline__ void l2_prefetch(const void* p, uint32_t bytes) { asm volatile("cp.async.bulk.prefetch.L2.global [%0], %1;" ::"l"(p), "r"(bytes) : "memory"); }
__device__ __forceinline__ void fence_async_smem() { asm volatile("fence.proxy.async.shared::cta;" ::: "memory"); }
__device__ __forceinline__ void bar_sync(int id, int n) { asm volatile("bar.sync %0, %1;" ::"r"(id), "r"(n) : "memory"); }
__device__ __forceinline__ void bar_arrive(int id, int n) { asm volatile("bar.arrive %0, %1;" ::"r"(id), "r"(n) : "memory"); }
__device__ __forceinline__ uint32_t lds32(uint32_t a) { uint32_t v; asm volatile("ld.shared.b32 %0, [%1];" : "=r"(v) : "r"(a) : "memory"); return v; }
__device__ __forceinline__ float2 lds64f(uint32_t a) { float2 v; asm volatile("ld.shared.v2.f32 {%0,%1}, [%2];" : "=f"(v.x), "=f"(v.y) : "r"(a) : "memory"); return v; }
__device__ __forceinline__ uint4 lds128(uint32_t a) { uint4 v; asm volatile("ld.shared.v4.b32 {%0,%1,%2,%3}, [%4];" : "=r"(v.x), "=r"(v.y), "=r"(v.z), "=r"(v.w) : "r"(a) : "memory"); return v; }
__device__ __forceinline__ float4 lds128f(uint32_t a) { float4 v; asm volatile("ld.shared.v4.f32 {%0,%1,%2,%3}, [%4];" : "=f"(v.x), "=f"(v.y), "=f"(v.z), "=f"(v.w) : "r"(a) : "memory"); return v; }
__device__ __forceinline__ void sts32(uint32_t a, uint32_t v) { asm volatile("st.shared.b32 [%0], %1;" ::"r"(a), "r"(v) : "memory"); }
__device__ __forceinline__ void sts64f(uint32_t a, float x, float y) { asm volatile("st.shared.v2.f32 [%0], {%1,%2};" ::"r"(a), "f"(x), "f"(y) : "memory"); }
__device__ __forceinline__ void sts128(uint32_t a, uint32_t x, uint32_t y, uint32_t z, uint32_t w) {
  asm volatile("st.shared.v4.b32 [%0], {%1,%2,%3,%4};" ::"r"(a), "r"(x), "r"(y), "r"(z), "r"(w) : "memory");
}
__device__ __forceinline__ void ldsm4(uint32_t (&r)[4], uint32_t a) {
  asm volatile("ldmatrix.sync.aligned.m8n8.x4.shared.b16 {%0,%1,%2,%3}, [%4];" : "=r"(r[0]), "=r"(r[1]), "=r"(r[2]), "=r"(r[3]) : "r"(a) : "memory");
}
__device__ __forceinline__ void stsm4t(uint32_t a, uint32_t r0, uint32_t r1, uint32_t r2, uint32_t r3) {
  asm volatile("stmatrix.sync.aligned.m8n8.x4.trans.shared.b16 [%0], {%1,%2,%3,%4};" ::"r"(a), "r"(r0), "r"(r1), "r"(r2), "r"(r3) : "memory");
}
__device__ __forceinline__ void stsm2t(uint32_t a, uint32_t r0, uint32_t r1) {
  asm volatile("stmatrix.sync.aligned.m8n8.x2.trans.shared.b16 [%0], {%1,%2};" ::"r"(a), "r"(r0), "r"(r1) : "memory");
}
__device__ __forceinline__ uint32_t pack_bf16(float lo, float hi) { uint32_t r; asm("cvt.rn.bf16x2.f32 %0, %1, %2;" : "=r"(r) : "f"(hi), "f"(lo)); return r; }
__device__ __forceinline__ float bf_lo(uint32_t v) { return __uint_as_float(v << 16); }
__device__ __forceinline__ float bf_hi(uint32_t v) { return __uint_as_float(v & 0xffff0000u); }
__device__ __forceinline__ uint32_t hfma2(uint32_t a, uint32_t b, uint32_t c) { uint32_t r; asm("fma.rn.bf16x2 %0, %1, %2, %3;" : "=r"(r) : "r"(a), "r"(b), "r"(c)); return r; }
__device__ __forceinline__ uint32_t hmul2(uint32_t a, uint32_t b) { uint32_t r; asm("mul.bf16x2 %0, %1, %2;" : "=r"(r) : "r"(a), "r"(b)); return r; }
__device__ __forceinline__ uint32_t hadd2(uint32_t a, uint32_t b) { uint32_t r; asm("add.bf16x2 %0, %1, %2;" : "=r"(r) : "r"(a), "r"(b)); return r; }
__device__ __forceinline__ float gelu_half(float hz) {
  float u = hz * fmaf(hz * hz, 8.f * 0.044715f * 0.7978845608028654f, 2.f * 0.7978845608028654f);
  float t;
  asm("tanh.approx.f32 %0, %1;" : "=f"(t) : "f"(u));
  return fmaf(hz, t, hz);
}
__device__ __forceinline__ uint64_t mkdesc(uint32_t addr, uint32_t lbo, uint32_t hi) { return (uint64_t)((addr >> 4) | ((lbo >> 4) << 16)) | ((uint64_t)hi << 32); }
#define WG_FENCE() asm volatile("wgmma.fence.sync.aligned;" ::: "memory")
#define WG_COMMIT() asm volatile("wgmma.commit_group.sync.aligned;" ::: "memory")
#define WG_WAIT(n) asm volatile("wgmma.wait_group.sync.aligned %0;" ::"n"(n) : "memory")
template <int N> __device__ __forceinline__ void reg_fence(float (&d)[N]) {
#pragma unroll
  for (int i = 0; i < N; i++) asm volatile("" : "+f"(d[i])::"memory");
}

__device__ __forceinline__ void wg_ss80n(float (&d)[40], uint64_t da, uint64_t db){
  asm volatile("wgmma.mma_async.sync.aligned.m64n80k16.f32.bf16.bf16 {%0,%1,%2,%3,%4,%5,%6,%7,%8,%9,%10,%11,%12,%13,%14,%15,%16,%17,%18,%19,%20,%21,%22,%23,%24,%25,%26,%27,%28,%29,%30,%31,%32,%33,%34,%35,%36,%37,%38,%39}, %40, %41, 1, 1, 1, 1, 1;"
   : "+f"(d[0]),"+f"(d[1]),"+f"(d[2]),"+f"(d[3]),"+f"(d[4]),"+f"(d[5]),"+f"(d[6]),"+f"(d[7]),"+f"(d[8]),"+f"(d[9]),"+f"(d[10]),"+f"(d[11]),"+f"(d[12]),"+f"(d[13]),"+f"(d[14]),"+f"(d[15]),"+f"(d[16]),"+f"(d[17]),"+f"(d[18]),"+f"(d[19]),"+f"(d[20]),"+f"(d[21]),"+f"(d[22]),"+f"(d[23]),"+f"(d[24]),"+f"(d[25]),"+f"(d[26]),"+f"(d[27]),"+f"(d[28]),"+f"(d[29]),"+f"(d[30]),"+f"(d[31]),"+f"(d[32]),"+f"(d[33]),"+f"(d[34]),"+f"(d[35]),"+f"(d[36]),"+f"(d[37]),"+f"(d[38]),"+f"(d[39])
   : "l"(da), "l"(db));
}
__device__ __forceinline__ void wg_ss80k(float (&d)[40], uint64_t da, uint64_t db){
  asm volatile("wgmma.mma_async.sync.aligned.m64n80k16.f32.bf16.bf16 {%0,%1,%2,%3,%4,%5,%6,%7,%8,%9,%10,%11,%12,%13,%14,%15,%16,%17,%18,%19,%20,%21,%22,%23,%24,%25,%26,%27,%28,%29,%30,%31,%32,%33,%34,%35,%36,%37,%38,%39}, %40, %41, 1, 1, 1, 1, 0;"
   : "+f"(d[0]),"+f"(d[1]),"+f"(d[2]),"+f"(d[3]),"+f"(d[4]),"+f"(d[5]),"+f"(d[6]),"+f"(d[7]),"+f"(d[8]),"+f"(d[9]),"+f"(d[10]),"+f"(d[11]),"+f"(d[12]),"+f"(d[13]),"+f"(d[14]),"+f"(d[15]),"+f"(d[16]),"+f"(d[17]),"+f"(d[18]),"+f"(d[19]),"+f"(d[20]),"+f"(d[21]),"+f"(d[22]),"+f"(d[23]),"+f"(d[24]),"+f"(d[25]),"+f"(d[26]),"+f"(d[27]),"+f"(d[28]),"+f"(d[29]),"+f"(d[30]),"+f"(d[31]),"+f"(d[32]),"+f"(d[33]),"+f"(d[34]),"+f"(d[35]),"+f"(d[36]),"+f"(d[37]),"+f"(d[38]),"+f"(d[39])
   : "l"(da), "l"(db));
}
__device__ __forceinline__ void wg_ss152k(float (&d)[76], uint64_t da, uint64_t db){
  asm volatile("wgmma.mma_async.sync.aligned.m64n152k16.f32.bf16.bf16 {%0,%1,%2,%3,%4,%5,%6,%7,%8,%9,%10,%11,%12,%13,%14,%15,%16,%17,%18,%19,%20,%21,%22,%23,%24,%25,%26,%27,%28,%29,%30,%31,%32,%33,%34,%35,%36,%37,%38,%39,%40,%41,%42,%43,%44,%45,%46,%47,%48,%49,%50,%51,%52,%53,%54,%55,%56,%57,%58,%59,%60,%61,%62,%63,%64,%65,%66,%67,%68,%69,%70,%71,%72,%73,%74,%75}, %76, %77, 1, 1, 1, 1, 0;"
   : "+f"(d[0]),"+f"(d[1]),"+f"(d[2]),"+f"(d[3]),"+f"(d[4]),"+f"(d[5]),"+f"(d[6]),"+f"(d[7]),"+f"(d[8]),"+f"(d[9]),"+f"(d[10]),"+f"(d[11]),"+f"(d[12]),"+f"(d[13]),"+f"(d[14]),"+f"(d[15]),"+f"(d[16]),"+f"(d[17]),"+f"(d[18]),"+f"(d[19]),"+f"(d[20]),"+f"(d[21]),"+f"(d[22]),"+f"(d[23]),"+f"(d[24]),"+f"(d[25]),"+f"(d[26]),"+f"(d[27]),"+f"(d[28]),"+f"(d[29]),"+f"(d[30]),"+f"(d[31]),"+f"(d[32]),"+f"(d[33]),"+f"(d[34]),"+f"(d[35]),"+f"(d[36]),"+f"(d[37]),"+f"(d[38]),"+f"(d[39]),"+f"(d[40]),"+f"(d[41]),"+f"(d[42]),"+f"(d[43]),"+f"(d[44]),"+f"(d[45]),"+f"(d[46]),"+f"(d[47]),"+f"(d[48]),"+f"(d[49]),"+f"(d[50]),"+f"(d[51]),"+f"(d[52]),"+f"(d[53]),"+f"(d[54]),"+f"(d[55]),"+f"(d[56]),"+f"(d[57]),"+f"(d[58]),"+f"(d[59]),"+f"(d[60]),"+f"(d[61]),"+f"(d[62]),"+f"(d[63]),"+f"(d[64]),"+f"(d[65]),"+f"(d[66]),"+f"(d[67]),"+f"(d[68]),"+f"(d[69]),"+f"(d[70]),"+f"(d[71]),"+f"(d[72]),"+f"(d[73]),"+f"(d[74]),"+f"(d[75])
   : "l"(da), "l"(db));
}
__device__ __forceinline__ void wg_rs64(float (&d)[32], const uint32_t (&a)[4], uint64_t db, int sd){
  asm volatile("{.reg .pred p; setp.ne.b32 p, %37, 0;\n"
   "wgmma.mma_async.sync.aligned.m64n64k16.f32.bf16.bf16 {%0,%1,%2,%3,%4,%5,%6,%7,%8,%9,%10,%11,%12,%13,%14,%15,%16,%17,%18,%19,%20,%21,%22,%23,%24,%25,%26,%27,%28,%29,%30,%31}, {%32,%33,%34,%35}, %36, p, 1, 1, 0;}"
   : "+f"(d[0]),"+f"(d[1]),"+f"(d[2]),"+f"(d[3]),"+f"(d[4]),"+f"(d[5]),"+f"(d[6]),"+f"(d[7]),"+f"(d[8]),"+f"(d[9]),"+f"(d[10]),"+f"(d[11]),"+f"(d[12]),"+f"(d[13]),"+f"(d[14]),"+f"(d[15]),"+f"(d[16]),"+f"(d[17]),"+f"(d[18]),"+f"(d[19]),"+f"(d[20]),"+f"(d[21]),"+f"(d[22]),"+f"(d[23]),"+f"(d[24]),"+f"(d[25]),"+f"(d[26]),"+f"(d[27]),"+f"(d[28]),"+f"(d[29]),"+f"(d[30]),"+f"(d[31])
   : "r"(a[0]),"r"(a[1]),"r"(a[2]),"r"(a[3]), "l"(db), "r"(sd));
}

#define CS(i)

template <int J, int Q0, int Q1> __device__ __forceinline__ void conv_mma(float (&d)[32], const uint32_t (&A)[16][4], uint64_t db) {
#pragma unroll
  for (int q = Q0; q <= Q1; q++)
#pragma unroll
    for (int s = 0; s < 4; s++) wg_rs64(d, A[4 * q + s], db + ((1024 * (J - q) - 32 * s) >> 4), (q | s) != 0);
}
template <int J>
__device__ __forceinline__ void conv_drain(float (&d)[32], float& c0, float& c1, uint32_t ex, uint32_t qc, uint32_t hst, int wg, int w, int lane) {
  reg_fence(d);
  float z[4] = {d[0] + c0, d[1] + c1, d[4] + d[2], d[5] + d[3]};
#pragma unroll
  for (int pp = 1; pp < 4; pp++)
    if (J < 3 || w + pp < 4)
      sts64f(ex + w * 768 + (J & 1) * 3072 + (pp - 1) * 256, __uint_as_float(pack_bf16(d[8 * pp] + d[8 * pp - 2], d[8 * pp + 1] + d[8 * pp - 1])),
             __uint_as_float(pack_bf16(d[8 * pp + 4] + d[8 * pp + 2], d[8 * pp + 5] + d[8 * pp + 3])));
  asm volatile("mov.b32 %0,%1;" : "=f"(c0) : "f"(d[30]));
  asm volatile("mov.b32 %0,%1;" : "=f"(c1) : "f"(d[31]));
  uint32_t v0[2], v1[2];
#pragma unroll
  for (int jj = 0; jj < 2; jj++) { v0[jj] = lds32(qc + (8 * J + jj) * 256); v1[jj] = lds32((qc ^ 32) + (8 * J + jj) * 256); }
  bar_sync(1 + wg, 128);
#pragma unroll
  for (int pp = 1; pp < 4; pp++) {
    const bool later = pp > w;
    if (J > 0 || !later) {
      const float2 u = lds64f(ex + ((w - pp) & 3) * 768 + (pp - 1) * 256 + (((J & 1) != 0) != later ? 3072 : 0));
      z[0] += bf_lo(__float_as_uint(u.x)); z[1] += bf_hi(__float_as_uint(u.x)); z[2] += bf_lo(__float_as_uint(u.y)); z[3] += bf_hi(__float_as_uint(u.y));
    }
  }
  const bool p = lane & 4, sw = lane & 2;
#pragma unroll
  for (int jj = 0; jj < 2; jj++) {
    const float recv = __shfl_xor_sync(0xffffffffu, p ? z[2 * jj] : z[2 * jj + 1], 4), keep = p ? z[2 * jj + 1] : z[2 * jj];
    const float ylo = p ? recv : keep, yhi = p ? keep : recv;
    const uint32_t qv = sw ? v1[jj] : v0[jj], cv = sw ? v0[jj] : v1[jj];
    sts32(hst + (8 * J + jj) * 128, pack_bf16(fmaf(bf_lo(qv), ylo, bf_lo(cv)), fmaf(bf_hi(qv), yhi, bf_hi(cv))));
  }
}
template <int I0> __device__ __forceinline__ void conv_load_a(uint32_t (&A)[16][4], uint32_t ta) {
#pragma unroll
  for (int i = I0; i < I0 + 8; i++) {
    const uint32_t a = ta - (i >> 2) * 1024 - (i & 3) * 32;
    A[i][0] = lds32(a); A[i][1] = lds32(a - 128); A[i][2] = lds32(a + 16); A[i][3] = lds32(a - 112);
  }
}

template <int KIND, int KS, int NWP, uint32_t WB, int WF, int WE, int RW, int NX, uint32_t XB, int XE, int NACC>
__device__ __forceinline__ void gemm_seg(float (&d)[NACC], uint32_t sb, int nch, uint32_t woff, uint32_t wi, uint32_t wmask, uint32_t xmask, bool waitx,
                                         int lt, int tok_arrive PROF_ARG) {
  const uint32_t bars = sb + BARS;
  const uint64_t la0 = mkdesc(sb + WR + woff, 1024, 0x40000040), lb0 = KIND == 0 ? mkdesc(sb + XR, 256, 0xC0000050) : mkdesc(sb + XR, 16, 0x40000040);
  uint32_t xi = 0, pw = 0, px = 0;
  uint32_t bw = bars + 8 * WF + 8 * wi, bx = bars + 8 * B_XF;
  constexpr bool RX = KIND == 1 || KIND == 2;
  if (waitx) mbar_wait2(bx, xmask & 1, bw, (wmask >> wi) & 1); else mbar_wait(bw, (wmask >> wi) & 1);
  reg_fence(d);
#pragma unroll 1
  for (int c = nch; c > 0; c--) {
    const uint64_t la = la0 + wi * (WB >> 4), lb = lb0 + xi * (XB >> 4);
    WG_FENCE();
#pragma unroll
    for (int k = 0; k < KS; k++) {
      if constexpr (KIND == 0) wg_ss80n(d, la + k * 128, lb + k * 160);
      else if constexpr (KIND == 1 || KIND == 3) wg_ss80k(d, la + k * 128, lb + (k >> 2) * 640 + (k & 3) * 2);
      else wg_ss152k(d, la + k * 128, lb + k * 2);
    }
    WG_COMMIT();
    const uint32_t rw = bw + 8 * (WE - WF), rx = bx + 8 * (XE - B_XF);
    wmask ^= 1u << wi;
    wi = wi + 1 == NWP ? 0 : wi + 1;
    if (KIND == 3) xi = xi + 1 == NX ? 0 : xi + 1;
    else if (KIND != 0) { xmask ^= 1u << xi; xi = xi + 1 == NX ? 0 : xi + 1; }
    else xi++;
    bw = bars + 8 * WF + 8 * wi; bx = bars + 8 * B_XF + 8 * (KIND == 0 ? xi >> 1 : xi);
    if (KIND == 0) waitx = !(xi & 1);
    if (c == 1) {
      if (tok_arrive >= 0) bar_arrive(tok_arrive, 256);
    } else if (PIPE_LATE) {
      WG_WAIT(1);
      if (lt < RW && pw) { mbar_arrive(pw); if (RX && lt == 0) mbar_arrive(px); }
      if (waitx) mbar_wait2(bx, (xmask >> xi) & 1, bw, (wmask >> wi) & 1); else mbar_wait(bw, (wmask >> wi) & 1);
    } else {
      if (waitx) mbar_wait2(bx, (xmask >> xi) & 1, bw, (wmask >> wi) & 1); else mbar_wait(bw, (wmask >> wi) & 1);
    }
    if (!PIPE_LATE || c == 1) {
      WG_WAIT(1);
      if (lt < RW && pw) { mbar_arrive(pw); if (RX && lt == 0) mbar_arrive(px); }
    }
    pw = rw; px = rx;
  }
  WG_WAIT(0);
  reg_fence(d);
  if (lt < RW) { mbar_arrive(pw); if (RX && lt == 0) mbar_arrive(px); }
}

__device__ __forceinline__ void gelu_pass(uint32_t a, uint32_t step, int n) {
  __syncwarp();
  uint4 v = lds128(a), v1 = lds128(a + step);
#pragma unroll 1
  for (; n > 0; n--, a += step) {
    uint4 v2 = v1;
    if (n > 2) v2 = lds128(a + 2 * step);
    sts128(a, pack_bf16(gelu_half(bf_lo(v.x)), gelu_half(bf_hi(v.x))), pack_bf16(gelu_half(bf_lo(v.y)), gelu_half(bf_hi(v.y))),
           pack_bf16(gelu_half(bf_lo(v.z)), gelu_half(bf_hi(v.z))), pack_bf16(gelu_half(bf_lo(v.w)), gelu_half(bf_hi(v.w))));
    v = v1; v1 = v2;
  }
}
#define GELU_INREG 1
__device__ __forceinline__ float act(float hz) { return GELU_INREG ? gelu_half(hz) : hz; }

__device__ __forceinline__ void pre_unit(uint32_t sb, int r, int j, int lane, float2 st0, float2 st1) {
  const int m_ = lane >> 3, rho = lane & 7, t = lane & 3;
  const uint32_t col = (j & 3) * 32 + (m_ >> 1) * 16, row = (m_ & 1) * 8 + rho;
  const uint32_t ka = sb + PK + r * 9216 + ((j >> 2) * 19 + row) * 128 + col;
  uint32_t k0[4], k1[4], k2[4], k3[4], vv[4], xx[4];
  ldsm4(k3, swz128(ka)); ldsm4(k2, swz128(ka + 128)); ldsm4(k1, swz128(ka + 256)); ldsm4(k0, swz128(ka + 384));
  ldsm4(vv, swz128(sb + PK + r * 9216 + 5120 + ((j >> 2) * 16 + row) * 128 + col));
  ldsm4(xx, swz128(sb + PX + ((2 * r + (j >> 2)) * 16 + row) * 128 + col));
  uint32_t kvr[4], qr[4], cr[4];
#pragma unroll
  for (int oc = 0; oc < 2; oc++) {
    const int ch = 128 * r + 16 * j + 8 * oc + 2 * t;
    const uint4 v = lds128(sb + PSK + ch * 8);
    const uint32_t dd = lds32(sb + PSK + 5120 + ch * 2);
    const uint32_t w0 = __byte_perm(v.x, v.z, 0x5410), w1 = __byte_perm(v.x, v.z, 0x7632), w2 = __byte_perm(v.y, v.w, 0x5410), w3 = __byte_perm(v.y, v.w, 0x7632);
#pragma unroll
    for (int th = 0; th < 2; th++) {
      const int m = 2 * oc + th;
      uint32_t ks = hmul2(k3[m], w3);
      ks = hfma2(k2[m], w2, ks);
      ks = hfma2(k1[m], w1, ks);
      ks = hfma2(k0[m], w0, ks);
      kvr[m] = hmul2(ks, vv[m]);
      const float mm = th ? st1.x : st0.x, rr = th ? st1.y : st0.y;
      const float xl = bf_lo(xx[m]), xh = bf_hi(xx[m]);
      const float ql = (xl - mm) * rr, qh = (xh - mm) * rr;
      qr[m] = pack_bf16(ql, qh);
      cr[m] = pack_bf16(fmaf(ql * bf_lo(dd), bf_lo(kvr[m]), xl), fmaf(qh * bf_hi(dd), bf_hi(kvr[m]), xh));
    }
  }
  const int ch = 16 * j + 8 * (m_ >> 1) + rho, th = m_ & 1;
  stsm4t(sb + EXCH + 12288 + r * 4096 + ch * 32 + ((th ^ ((ch >> 2) & 1)) << 4), kvr[0], kvr[1], kvr[2], kvr[3]);
  const uint32_t qa = sb + QCB(r) + ch * 64;
  const int sx = (ch >> 1) & 3;
  stsm4t(qa + ((th ^ sx) << 4), qr[0], qr[1], qr[2], qr[3]);
  stsm4t(qa + (((2 + th) ^ sx) << 4), cr[0], cr[1], cr[2], cr[3]);
}
__device__ __forceinline__ void build_table(uint32_t sb, int r, int lt) {
  const uint32_t tb = sb + TABB(r), raw = sb + UB(r) + 128;
#pragma unroll
  for (int i = 0; i < 2; i++) {
    const int s = lt + 128 * i;
    const uint4 v = lds128(raw + s * 16);
    const uint32_t pv = lds32(raw + s * 16 - 4);
    sts128(tb + TAB_O + (1020 - 4 * s) * 4, __byte_perm(v.w, 0, 0x1032), __byte_perm(v.z, 0, 0x1032), __byte_perm(v.y, 0, 0x1032), __byte_perm(v.x, 0, 0x1032));
    sts128(tb + TAB_E + (1021 - 4 * s) * 4, __byte_perm(v.w, v.z, 0x7610), __byte_perm(v.z, v.y, 0x7610), __byte_perm(v.y, v.x, 0x7610), __byte_perm(v.x, pv, 0x7610));
  }
  if (lt < 7) sts32(tb + (lt < 3 ? TAB_E + (1025 + lt) * 4 : TAB_O + (1021 + lt) * 4), 0);
}
__device__ __forceinline__ void warp_signal(uint32_t bar, int lane) {
  fence_async_smem();
  __syncwarp();
  if (lane == 0) mbar_arrive(bar);
}

__device__ __forceinline__ void filter_load(const Params& p, uint32_t sb, int b, int r) {
  mbar_expect(sb + BARS + 8 * (B_F + r), 4096);
  bulk_load(sb + UB(r) + 128, p.ssm_k + (size_t)(128 * r + b) * S_, 4096, sb + BARS + 8 * (B_F + r));
}
__device__ __forceinline__ void front_load(const Params& p, uint32_t sb, int b, int r) {
  const uint32_t bars = sb + BARS;
  mbar_expect(bars + 8 * (B_KV + r), 4864 + 4096);
  tma_load3(sb + PK + r * 9216, &p.kin, 0, 16 * b - 3, 2 * r, bars + 8 * (B_KV + r));
  tma_load3(sb + PK + r * 9216 + 5120, &p.vin, 0, 16 * b, 2 * r, bars + 8 * (B_KV + r));
  if (!DEFER_F || r < 2) filter_load(p, sb, b, r);
}

__global__ void __launch_bounds__(NTHR, 1) fused_kernel(const __grid_constant__ Params p) {
  extern __shared__ __align__(1024) uint8_t smem_raw[];
  const uint32_t sb = (uint32_t)__cvta_generic_to_shared(smem_raw);
  const int tid = threadIdx.x, lane = tid & 31;
  const int warp = __shfl_sync(0xffffffffu, tid >> 5, 0);
  const int wg = warp >> 2;
  const int b = blockIdx.x;
  const uint32_t bars = sb + BARS;
  if (warp >= 12) {
    if (warp == 13 && b >= 128 && elect()) {
      mbar_init(bars + 8 * B_X, 1);
      mbar_expect(bars + 8 * B_X, 204800);
      bulk_load(sb, p.pw1 + (b - 128) * 160 * D_, 102400, bars + 8 * B_X);
      bulk_load(sb + 102400, p.pw1 + ((b - 128) * 160 + 80) * D_, 102400, bars + 8 * B_X);
    }
    if (warp < 14 && b < 128 && elect()) {
      if (warp == 13) {
        mbar_init(bars + 8 * B_X, 1);
        mbar_expect(bars + 8 * B_X, 20480 + 5120 + 1280);
        tma_load3(sb + PX, &p.xin, 0, 16 * b, 0, bars + 8 * B_X);
        bulk_load(sb + PSK, p.shift_k, 5120, bars + 8 * B_X);
        bulk_load(sb + PSK + 5120, p.ssm_D, 1280, bars + 8 * B_X);
      }
#pragma unroll 1
      for (int r = warp - 12; r < 5; r += 2) { mbar_init(bars + 8 * (B_KV + r), 1); mbar_init(bars + 8 * (B_F + r), 1); front_load(p, sb, b, r); }
    }
  } else {
    const int i = B_U + warp + 12 * lane;
    if (i < B_NUM) {
      uint32_t cnt = 1;
      if (i >= B_PST && i < B_HST) cnt = 8;
      else if ((i >= B_HST && i < B_HDONE) || (i >= B_SG && i < B_SD) || (i >= B_SS && i < B_WF1)) cnt = 4;
      else if (i == B_XFREE || (i >= B_X3E && i < B_WF4) || (i >= B_WE3 && i < B_XF)) cnt = 3;
      else if ((i >= B_XE && i < B_X3E) || (i >= B_WE2 && i < B_WF3) || (i >= B_WF4 && i < B_STRAW)) cnt = 2;
      mbar_init(bars + 8 * i, cnt);
    }
  }
  if (tid < 40 && b < 128) sts128(sb + UB(tid >> 3) + (tid & 7) * 16, 0, 0, 0, 0);
  asm volatile("{.reg .pred p; setp.ne.u32 p, %0, 0; @p trap;}" ::"r"(sb & 1023));
  __syncthreads();

  const int ti = b / 5, fj = b % 5;
  const int t3 = MAP3 ? (b / 3) % 14 : b / 9, f3 = MAP3 ? b / 42 * 3 + b % 3 : b % 9;

  if (wg == 3) {
    asm volatile("setmaxnreg.dec.sync.aligned.u32 32;");
    if (b < 130) {
      if (warp == 12) {
        if (b < 128) {
          mbar_wait(bars + 8 * (B_QC + 1), 0);
          if (elect()) {
            l2_prefetch(reinterpret_cast<const uint8_t*>(p.pw1) + b * 6400, 6400);
            l2_prefetch(reinterpret_cast<const uint8_t*>(p.pw2) + b * 6400, 6400);
            l2_prefetch(reinterpret_cast<const uint8_t*>(p.pw3) + b * 17280, 17280);
            l2_prefetch(reinterpret_cast<const uint8_t*>(p.pw4) + b * 17280, 17280);
          }
          mbar_wait(bars + 8 * B_HDONE, 0);
        } else {
          mbar_wait(bars + 8 * B_CS, 0);
        }
#pragma unroll 1
        for (int n = 0; n < 20; n++) {
          const uint32_t q = n & 3;
          mbar_wait(bars + 8 * (B_WE2 + q), ((n >> 2) & 1) ^ 1);
          if (elect()) {
            mbar_expect(bars + 8 * (B_WF2 + q), 16384);
            if (n < 10) tma_load3(sb + WR + q * 16384, &p.w1p, 0, 64 * n, 2 * fj, bars + 8 * (B_WF2 + q));
            else tma_load2(sb + WR + q * 16384, &p.w2d, 128 * fj + (n < 15 ? 0 : 64), 128 * (n < 15 ? n - 10 : n - 15), bars + 8 * (B_WF2 + q));
          }
        }
        if (b < 126) {
#pragma unroll 1
          for (int i = 0; i < 5; i++) {
            const uint32_t q = i < 3 ? i : i - 3;
            mbar_wait(bars + 8 * (i < 3 ? B_WE2 + 1 + i : B_WE3 + q), 0);
            if (elect()) { mbar_expect(bars + 8 * (B_WF3 + q), 24576); tma_load3(sb + WR + q * 24576, &p.w3t, 0, 128 * i, 3 * f3, bars + 8 * (B_WF3 + q)); }
          }
          int k = 64, f = 192 * f3;
          uint32_t s = 6;
#pragma unroll 1
          for (int j = 0; j < 15; j++) {
            mbar_wait(bars + 8 * (j < 3 ? B_WE3 + 2 : j < 6 ? B_WE3 : j < 9 ? B_WE3 + 1 : B_WE1 + s), j >= 3 && j < 9);
            if (elect()) { mbar_expect(bars + 8 * (B_WF1 + s), 8192); tma_load2(sb + WR + s * 8192, &p.w3, f, k, bars + 8 * (B_WF1 + s)); }
            k += 128;
            if (k == 704) { k = 64; f += 64; }
            if (++s == 9) s = 0;
          }
        }
        {
          int k = 0;
          uint32_t q = 4, par = 1;
#pragma unroll 1
          for (int i = 0; i < 27; i++) {
            if (i >= 6) mbar_wait(bars + 8 * (B_WE4 + q), par);
            else if (b >= 126) { if (i == 0) { mbar_wait(bars + 8 * (B_WE2 + 3), 0); mbar_wait(bars + 8 * (B_XE + 4), 0); } }
            else if (i < 2 || i >= 4) mbar_wait(bars + 8 * (B_WE1 + ((0x210075u >> (4 * i)) & 15u)), i >= 1);
            else if (i == 2) mbar_wait(bars + 8 * (B_X3E + 4), 1);
            if (elect()) {
              mbar_expect(bars + 8 * (B_WF4 + q), 16384);
              tma_load3(sb + WR - 32768 + q * 16384, &p.w4p, 0, k, 2 * fj, bars + 8 * (B_WF4 + q));
            }
            k += 192;
            if (k >= F_) k -= F_ - 64;
            if (++q == 6) q = 0;
            if (q == 4) par ^= 1;
          }
        }
      } else if (warp == 13) {
        unsigned ep;
        asm volatile("ld.relaxed.gpu.global.u32 %0, [%1];" : "=r"(ep) : "l"(&g_epoch) : "memory");
        ep += 1;
        if (lane < 5) mbar_expect(bars + 8 * (B_XF + lane), 20480);
        if (b < 128) {
          if (lane < 10) mbar_expect(bars + 8 * (B_U + lane), lane < 5 ? 4096 : 8192);
          poll1(&g_flag[F_P * 32], ep * 128u);
          if (lane == 0) STAMP(20);
#pragma unroll 1
          for (int r = 0; r < 5; r++) {
            mbar_wait(bars + 8 * (B_TAB + r), 0);
            if (elect()) {
              const int c = 128 * r + b;
              bulk_load(sb + UB(r) + 128, g_kvT + (size_t)c * S_, 4096, bars + 8 * (B_U + r));
              bulk_load(sb + QCB(r), g_qc + (size_t)c * S_ * 2, 8192, bars + 8 * (B_QC + r));
            }
          }
        } else {
          mbar_wait(bars + 8 * B_CS, 0);
        }
#pragma unroll 1
        for (int r = 0; r < 5; r++) {
          if (b < 128) mbar_wait(bars + 8 * (B_HDONE + r), 0);
          poll1(&g_flag[(F_C + r) * 32], ep * (r == 0 ? 132u : 128u));
          if (elect()) {
            bulk_load(sb + XR + r * 20480, g_hT + (size_t)ti * (D_ * TT) + r * 10240, 20480, bars + 8 * (B_XF + r));
            if (r >= 3) STAMPV(83, r);
          }
        }
        mbar_wait(bars + 8 * B_XFREE, 0);
        if (lane < 5) mbar_expect(bars + 8 * (B_XF + lane), 20480);
        if (GLOBAL_F1) poll1(&g_flag[F_1 * 32], ep * 260u);
        else poll3(&g_flag[(F_1 + max(ti - 1, 0)) * 32], &g_flag[(F_1 + ti) * 32], &g_flag[(F_1 + min(ti + 1, 25)) * 32], ep * 10u);
        align_time(AL1);
#pragma unroll 1
        for (int i = 0; i < 5; i++) {
          if (elect()) {
            tma_load3(sb + XR + i * 20480, &p.hsL, 0, TT * ti, 2 * i, bars + 8 * (B_XF + i));
            if (i == 0) STAMP(27);
          }
        }
        if (b < 126) {
          const int t0 = (TT3 * t3) / TT, t2 = min((TT3 * t3 + TT3 - 1) / TT, 25);
#pragma unroll 1
          for (int h = 0; h < 2; h++) {
            if (GLOBAL_F2) poll1(&g_flag[(F_2 + h) * 32], ep * 130u);
            else poll3(&g_flag[(F_2 + 2 * t0 + h) * 32], &g_flag[(F_2 + 2 * (t0 + 1) + h) * 32], &g_flag[(F_2 + 2 * t2 + h) * 32], ep * 5u);
            if (h == 0) align_time(AL2);
            if (lane == 0) STAMPV(29, h);
#pragma unroll 1
            for (int s = 0; s < 5; s++) {
              mbar_wait(bars + 8 * ((h ? B_X3E : B_XE) + s), 0);
              if (elect()) {
                mbar_expect(bars + 8 * (B_XF + s), TT3 * 128);
                tma_load2(sb + XR + s * 19456, &p.x1L, 128 * s + 64 * h, TT3 * t3, bars + 8 * (B_XF + s));
              }
            }
          }
        }
        {
          const unsigned* f0 = &g_flag[(F_3 + (GLOBAL_F3 ? 0 : 3 * ((TT * ti) / TT3))) * 32];
          const unsigned* f1 = &g_flag[(F_3 + (GLOBAL_F3 ? 0 : 3 * min((TT * ti + TT - 1) / TT3, 13))) * 32];
          uint32_t s = 0, q = 4, par = 1;
          if (b >= 126) mbar_wait(bars + 8 * (B_XE + 4), 0);
#pragma unroll 1
          for (int cl = 0; cl < 3; cl++) {
            if (GLOBAL_F3) poll1(f0 + cl * 32, ep * 126u); else poll3(f0 + cl * 32, f1 + cl * 32, f1 + cl * 32, ep * 9u);
            if (cl == 0) align_time(AL3);
            if (lane == 0) STAMPV(33, cl);
#pragma unroll 1
            for (int k = 64 * cl; k < F_; k += 192) {
              if (cl || k >= 6 * 192) mbar_wait(bars + 8 * (B_WE4 + q), par);
              else if (b < 126) mbar_wait(bars + 8 * (B_X3E + ((s + 1) >> 1)), 1);
              if (elect()) {
                mbar_expect(bars + 8 * (B_WF4 + q), 10240);
                tma_load2(sb + XR + s * 10240, &p.HL, k, TT * ti, bars + 8 * (B_WF4 + q));
              }
              if (++q == 6) q = 0;
              if (++s == 6) { s = 0; par ^= 1; }
            }
          }
        }
        if (b == 0 && lane == 0) asm volatile("st.relaxed.gpu.global.u32 [%0], %1;" ::"l"(&g_epoch), "r"(ep) : "memory");
      } else {
        const int sw = warp - 14;
        if (TMPF && sw && lane < 17) asm volatile("prefetch.tensormap [%0];" ::"l"(&p.w1p + lane) : "memory");
        if (b < 128) {
          if (!sw) {
#pragma unroll 1
            for (int r = 0; r < 5; r++) {
              mbar_wait(bars + 8 * (B_PST + r), 0);
              if (lane == 0) {
                tma_store2(&p.kvT, 16 * b, 128 * r, sb + EXCH + 12288 + r * 4096);
                tma_store2(&p.qc, 32 * b, 128 * r, sb + QCB(r));
              }
              __syncwarp();
            }
            if (lane == 0) {
              store_commit_wait();
              STAMP(37);
              flag_release(&g_flag[F_P * 32]);
              STAMP(36);
              if (DEFER_F) { filter_load(p, sb, b, 2); filter_load(p, sb, b, 3); filter_load(p, sb, b, 4); }
            }
            __syncwarp();
          }
          if (sw) {
#pragma unroll 1
            for (int r = 0; r < 5; r++) {
              mbar_wait(bars + 8 * (B_HST + r), 0);
              if (elect()) {
                if (r == 4) STAMP(73);
                const int ch = 128 * r + b;
                tma_store5(&p.hT, 0, ch & 7, 0, ch >> 3, 0, sb + TABB(r));
                store_commit_wait();
                mbar_arrive(bars + 8 * (B_HDONE + r));
                flag_release(&g_flag[(F_C + r) * 32]);
                if (r == 0 || r >= 3) STAMPV(3, r);
              }
              __syncwarp();
            }
          }
        }
        const uint32_t stg = sb + GST + sw * 19456;
        mbar_wait(bars + 8 * (B_SG + sw), 0);
        if (elect()) {
#pragma unroll 1
          for (int hf = 0; hf < 2; hf++) {
            const int f = 128 * fj + 64 * sw + 32 * hf, grp = f / 160;
            tma_store2(&p.hsS, f, TT * ti + (grp == 0 ? 3 : grp == 1 ? 1 : grp == 2 ? 4 : 0), stg + hf * 5120);
          }
          store_commit_wait();
          mbar_arrive(bars + 8 * (B_SD + sw));
          flag_release(&g_flag[(F_1 + (GLOBAL_F1 ? 0 : ti)) * 32]);
          STAMPV(10, sw);
        }
        __syncwarp();
        mbar_wait(bars + 8 * (B_SG + sw), 1);
        if (lane == 0) {
          tma_store2(&p.x1S, 128 * fj + 64 * sw, TT * ti, stg);
          if (!sw) {
            store_commit_wait();
            mbar_arrive(bars + 8 * B_SD);
            flag_release(&g_flag[(F_2 + (GLOBAL_F2 ? 0 : 2 * ti)) * 32]);
            STAMP(14);
          }
        }
        __syncwarp();
        mbar_wait(bars + 8 * (B_SS + sw), 0);
        if (lane == 0) {
          bulk_store(g_st + (2 * fj + sw) * 2176 + TT * ti, sb + XST + sw * 640, 640);
          store_commit_wait();
          if (sw) mbar_arrive(bars + 8 * (B_SD + 1));
          flag_release(&g_flag[(F_S + ti) * 32]);
          if (sw) { flag_add(&g_flag[(F_2 + (GLOBAL_F2 ? 0 : 2 * ti) + 1) * 32]); STAMP(15); }
        }
        __syncwarp();
        if (b < 126) {
          if (sw) {
            unsigned ep;
            asm volatile("ld.relaxed.gpu.global.u32 %0, [%1];" : "=r"(ep) : "l"(&g_epoch) : "memory");
            poll3(&g_flag[(F_S + (TT3 * t3) / TT) * 32], &g_flag[(F_S + (TT3 * t3) / TT + 1) * 32], &g_flag[(F_S + min((TT3 * t3 + TT3 - 1) / TT, 25)) * 32], (ep + 1) * 10u);
            if (elect()) {
              mbar_expect(bars + 8 * B_STRAW, 10 * 1232);
              tma_load2(sb + STRAW, &p.stL, (TT3 * t3) & ~1, 0, bars + 8 * B_STRAW);
            }
            mbar_wait(bars + 8 * B_STRAW, 0);
#pragma unroll 1
            for (int r = lane; r < 152; r += 32) {
              float s = 0.f, ss = 0.f;
#pragma unroll
              for (int i = 0; i < 10; i++) { const float2 v = lds64f(sb + STRAW + i * 1232 + (r + (t3 & 1)) * 8); s += v.x; ss += v.y; }
              const float m = s * (1.f / D_);
              const float rs = 0.5f * rsqrtf(fmaxf(ss * (1.f / D_) - m * m, 0.f) + EPS);
              sts64f(sb + ST3 + r * 8, rs, -m * rs);
            }
            __syncwarp();
            if (lane == 0) { mbar_arrive(bars + 8 * B_ST3); STAMP(43); }
          }
#pragma unroll 1
          for (int w = sw; w < 3; w += 2) {
            mbar_wait(bars + 8 * (B_SG + w), 0);
            if (elect()) {
              STAMPV(21, w);
              tma_store2(&p.HS, 192 * f3 + 64 * w, TT3 * t3, stg);
              store_commit_wait();
              STAMPV(24, w);
              mbar_arrive(bars + 8 * (B_SD + w));
              flag_release(&g_flag[(F_3 + (GLOBAL_F3 ? 0 : 3 * t3) + w) * 32]);
              STAMPV(44, w);
            }
            __syncwarp();
          }
        }
        mbar_wait(bars + 8 * (B_SG + sw), b < 126);
        if (elect()) {
          tma_store2(&p.outS, 128 * fj + 64 * sw, TT * ti, stg);
          store_commit_wait();
          STAMPV(49, sw);
        }
      }
    }
    __syncwarp();
    PROF_END();
  } else {
    asm volatile("setmaxnreg.inc.sync.aligned.u32 160;");
    const int w = warp & 3, g = lane >> 2, t = lane & 3, lt = tid & 127;
    const bool lead = lt == 0;
    if (b >= 128) {
      mbar_wait(bars + 8 * B_X, 0);
      if (tid < 320) {
        float a0 = 0.f, a1 = 0.f;
#pragma unroll 16
        for (int r = 0; r < 160; r++) { const uint32_t v = lds32(sb + r * 1280 + tid * 4); a0 += bf_lo(v); a1 += bf_hi(v); }
        reinterpret_cast<float2*>(g_cs1)[(b - 128) * 320 + tid] = make_float2(a0, a1);
        __threadfence();
      }
      bar_sync(7, 384);
      if (tid == 0) { flag_add(&g_flag[F_C * 32]); mbar_arrive(bars + 8 * B_CS); STAMP(68); }
    } else {
      mbar_wait(bars + 8 * B_X, 0);
      if (tid == 0) STAMP(1);
      if (warp < 8) {
        const int row = 2 * warp + (lane >> 4);
        float xv[40];
#pragma unroll
        for (int i = 0; i < 5; i++) {
          uint4 v = lds128(sb + PX + ((2 * i + ((lane >> 3) & 1)) * 16 + row) * 128 + (lane & 7) * 16);
          xv[8 * i] = bf_lo(v.x); xv[8 * i + 1] = bf_hi(v.x); xv[8 * i + 2] = bf_lo(v.y); xv[8 * i + 3] = bf_hi(v.y);
          xv[8 * i + 4] = bf_lo(v.z); xv[8 * i + 5] = bf_hi(v.z); xv[8 * i + 6] = bf_lo(v.w); xv[8 * i + 7] = bf_hi(v.w);
        }
        float s0 = 0.f, s1 = 0.f, s2 = 0.f, s3 = 0.f;
#pragma unroll
        for (int i = 0; i < 40; i += 4) { s0 += xv[i]; s1 += xv[i + 1]; s2 += xv[i + 2]; s3 += xv[i + 3]; }
        float s = (s0 + s1) + (s2 + s3);
#pragma unroll
        for (int o = 8; o; o >>= 1) s += __shfl_xor_sync(0xffffffffu, s, o);
        const float m = s * (1.f / D_);
        s0 = s1 = s2 = s3 = 0.f;
#pragma unroll
        for (int i = 0; i < 40; i += 4) {
          const float a0 = xv[i] - m, a1 = xv[i + 1] - m, a2 = xv[i + 2] - m, a3 = xv[i + 3] - m;
          s0 = fmaf(a0, a0, s0); s1 = fmaf(a1, a1, s1); s2 = fmaf(a2, a2, s2); s3 = fmaf(a3, a3, s3);
        }
        s = (s0 + s1) + (s2 + s3);
#pragma unroll
        for (int o = 8; o; o >>= 1) s += __shfl_xor_sync(0xffffffffu, s, o);
        if ((lane & 15) == 0) sts64f(sb + ROWST + row * 8, m, rsqrtf(s * (1.f / D_) + EPS));
      }
      bar_sync(7, 384);
      {
        const float2 st0 = lds64f(sb + ROWST + g * 8), st1 = lds64f(sb + ROWST + (8 + g) * 8);
#pragma unroll 1
        for (int u = warp; u < 40; u += 12) {
          mbar_wait(bars + 8 * (B_KV + (u >> 3)), 0);
          pre_unit(sb, u >> 3, u & 7, lane, st0, st1);
          warp_signal(bars + 8 * (B_PST + (u >> 3)), lane);
        }
        if (tid == 0) STAMP(2);
#pragma unroll 1
        for (int r = wg; r < (wg < 2 ? wg + 1 : 5); r++) {
          mbar_wait(bars + 8 * (B_F + r), 0);
          build_table(sb, r, lt);
          bar_sync(1 + wg, 128);
          if (lead) mbar_arrive(bars + 8 * (B_TAB + r));
        }
      }
      {
        uint32_t tid2;
        asm volatile("mov.u32 %0, %%tid.x;" : "=r"(tid2));
        const int lane = tid2 & 31, g = lane >> 2, t = lane & 3;
        const uint32_t ex = sb + EXCH + wg * 12288 + lane * 8;
        const int L0 = 128 * w + 8 + g;
        const uint32_t ta0 = sb + ((g & 1) ? TAB_O + ((2047 - L0) / 2 + t) * 4 : TAB_E + ((2048 - L0) / 2 + t) * 4);
        uint32_t A[16][4];
        conv_load_a<0>(A, ta0 + TABB(wg));
        conv_load_a<8>(A, ta0 + TABB(wg));
        const uint32_t qc0 = sb + w * 512 + t * 64 + (t >= 2 ? 32 : 0) + (g & 1) * 16 + (g >> 1) * 4;
        const uint32_t hst0 = sb + w * 256 + t * 32 + (((g & 1) ^ ((b >> 2) & 1)) << 4) + (g >> 1) * 4;
#pragma unroll 1
        for (int r = wg; r < 5; r += 3) {
          const uint64_t db = mkdesc(sb + UB(r) + 128 - 16, 16, 0x8);
          const int nxa = CORDER == 0 ? (r == 0 ? 1 : r == 1 ? 0 : r == 2 ? 1 : r == 3 ? 2 : 0)
                        : CORDER == 1 ? (r == 0 ? 1 : r == 1 ? 0 : r == 2 ? 1 : r == 3 ? 1 : 0) : (r == 0 ? 1 : r == 1 ? 2 : r == 2 ? 0 : r == 3 ? 1 : 0);
          const int nxb = CORDER == 0 ? (r == 0 ? 2 : r == 1 ? 0 : 1) : CORDER == 1 ? (r == 0 ? 2 : r == 1 ? 2 : r == 2 ? 0 : 1) : (r == 0 ? 1 : r == 1 ? 2 : r == 2 ? 0 : 1);
          float d0[32], d1[32], c0 = 0.f, c1 = 0.f;
          const uint32_t qc = qc0 + QCB(r), hst = hst0 + TABB(r);
          if (!AEARLY && r >= 3) { mbar_wait(bars + 8 * (B_TAB + r), 0); conv_load_a<0>(A, ta0 + TABB(r)); }
          mbar_wait(bars + 8 * (B_U + r), 0);
          if (r > 0) bar_sync(4 + wg, 256);
          WG_FENCE();
          conv_mma<0, 0, 0>(d0, A, db);
          WG_COMMIT();
          conv_mma<1, 0, 1>(d1, A, db);
          WG_COMMIT();
          bar_arrive(4 + nxa, 256);
          if (r >= 3) conv_load_a<8>(A, ta0 + TABB(r));
          mbar_wait(bars + 8 * (B_QC + r), 0);
          WG_WAIT(1);
          conv_drain<0>(d0, c0, c1, ex, qc, hst, wg, w, lane);
          WG_WAIT(0);
          conv_drain<1>(d1, c0, c1, ex, qc, hst, wg, w, lane);
          bar_sync(4 + wg, 256);
          WG_FENCE();
          if (AEARLY) {
            conv_mma<2, 0, 1>(d0, A, db);
            conv_mma<3, 0, 1>(d1, A, db);
            WG_COMMIT();
            conv_mma<2, 2, 2>(d0, A, db);
            WG_COMMIT();
            conv_mma<3, 2, 3>(d1, A, db);
          } else {
            conv_mma<2, 0, 2>(d0, A, db);
            WG_COMMIT();
            conv_mma<3, 0, 3>(d1, A, db);
          }
          WG_COMMIT();
          if (r < 4) bar_arrive(4 + nxb, 256);
          if (AEARLY && r < 2) {
            mbar_wait(bars + 8 * (B_TAB + r + 3), 0);
            WG_WAIT(2);
            conv_load_a<0>(A, ta0 + TABB(r + 3));
          }
          WG_WAIT(1);
          conv_drain<2>(d0, c0, c1, ex, qc, hst, wg, w, lane);
          WG_WAIT(0);
          conv_drain<3>(d1, c0, c1, ex, qc, hst, wg, w, lane);
          warp_signal(bars + 8 * (B_HST + r), lane);
        }
      }
    }
    if (b < 130) {
      uint32_t res[20];
      uint32_t tid2;
      asm volatile("mov.u32 %0, %%tid.x;" : "=r"(tid2));
      const int lane = tid2 & 31, g = lane >> 2, t = lane & 3, lt = tid2 & 127;
      const bool lead = lt == 0;
      const int m_ = lane >> 3, rho = lane & 7;
      const uint32_t stg = sb + GST + (wg & 1) * 19456;
      if (wg == 2) {
        float s[8], ss[8];
#pragma unroll
        for (int i = 0; i < 8; i++) { s[i] = 0.f; ss[i] = 0.f; }
        mbar_wait(bars + 8 * B_XF, 0);
        {
          const float* cp = g_cs1 + 128 * fj + lt;
          sts32(sb + CS1S + lt * 4, __float_as_uint((__ldcg(cp) + __ldcg(cp + D_)) + (__ldcg(cp + 2 * D_) + __ldcg(cp + 3 * D_))));
        }
        if (STATS_LATE && b < 128) mbar_wait(bars + 8 * (B_HST + 4), 0);
        if (w < 3) {
          const bool act = lt < 80;
#pragma unroll 1
          for (int c = 0; c < 10; c++) {
            const uint32_t sl = c;
            if (!(c & 1)) mbar_wait(bars + 8 * (B_XF + (c >> 1)), 0);
            if (act) {
              {
                uint4 v[8];
#pragma unroll
                for (int k1 = 0; k1 < 8; k1++) v[k1] = lds128(sb + XR + sl * 10240 + k1 * 1280 + lt * 16);
                if (SPACK) {
#pragma unroll
                  for (int e = 0; e < 4; e++) {
                    uint32_t u[8];
#pragma unroll
                    for (int k1 = 0; k1 < 8; k1++) u[k1] = e == 0 ? v[k1].x : e == 1 ? v[k1].y : e == 2 ? v[k1].z : v[k1].w;
                    const uint32_t a = hadd2(hadd2(hadd2(u[0], u[1]), hadd2(u[2], u[3])), hadd2(hadd2(u[4], u[5]), hadd2(u[6], u[7])));
                    const uint32_t q = hadd2(hfma2(u[3], u[3], hfma2(u[2], u[2], hfma2(u[1], u[1], hmul2(u[0], u[0])))),
                                             hfma2(u[7], u[7], hfma2(u[6], u[6], hfma2(u[5], u[5], hmul2(u[4], u[4])))));
                    s[2 * e] += bf_lo(a); s[2 * e + 1] += bf_hi(a); ss[2 * e] += bf_lo(q); ss[2 * e + 1] += bf_hi(q);
                  }
                } else {
#pragma unroll
                  for (int k1 = 0; k1 < 8; k1++) {
                    float f;
                    f = bf_lo(v[k1].x); s[0] += f; ss[0] = fmaf(f, f, ss[0]); f = bf_hi(v[k1].x); s[1] += f; ss[1] = fmaf(f, f, ss[1]);
                    f = bf_lo(v[k1].y); s[2] += f; ss[2] = fmaf(f, f, ss[2]); f = bf_hi(v[k1].y); s[3] += f; ss[3] = fmaf(f, f, ss[3]);
                    f = bf_lo(v[k1].z); s[4] += f; ss[4] = fmaf(f, f, ss[4]); f = bf_hi(v[k1].z); s[5] += f; ss[5] = fmaf(f, f, ss[5]);
                    f = bf_lo(v[k1].w); s[6] += f; ss[6] = fmaf(f, f, ss[6]); f = bf_hi(v[k1].w); s[7] += f; ss[7] = fmaf(f, f, ss[7]);
                  }
                }
              }
            }
          }
          const int k0 = (lt >> 1) & 7, half = (lt & 1) ^ (k0 >> 2);
#pragma unroll
          for (int i = 0; i < 4; i++) {
            const bool up = k0 & 4;
            const float a = up ? s[i] : s[i + 4], c = up ? ss[i] : ss[i + 4];
            s[i] = (up ? s[i + 4] : s[i]) + __shfl_xor_sync(0xffffffffu, a, 9);
            ss[i] = (up ? ss[i + 4] : ss[i]) + __shfl_xor_sync(0xffffffffu, c, 9);
          }
#pragma unroll
          for (int i = 0; i < 2; i++) {
            const bool up = k0 & 2;
            const float a = up ? s[i] : s[i + 2], c = up ? ss[i] : ss[i + 2];
            s[i] = (up ? s[i + 2] : s[i]) + __shfl_xor_sync(0xffffffffu, a, 4);
            ss[i] = (up ? ss[i + 2] : ss[i]) + __shfl_xor_sync(0xffffffffu, c, 4);
          }
          {
            const bool up = k0 & 1;
            const float a = up ? s[0] : s[1], c = up ? ss[0] : ss[1];
            s[0] = (up ? s[1] : s[0]) + __shfl_xor_sync(0xffffffffu, a, 2);
            ss[0] = (up ? ss[1] : ss[0]) + __shfl_xor_sync(0xffffffffu, c, 2);
          }
          if (act) {
            const float m = s[0] * (1.f / D_);
            const float var = fmaxf(ss[0] * (1.f / D_) - m * m, 0.f);
            const float r2 = rsqrtf(var + EPS);
            const int tok = (lt >> 4) * 16 + half * 8 + k0;
            const float r23 = TT * ti + tok < S_ ? 0.5f * r2 * rsqrtf(var * r2 * r2 + EPS) : 0.f;
            sts128(sb + TOKST + tok * 16, __float_as_uint(r2), __float_as_uint(-m * r2), __float_as_uint(r23), __float_as_uint(-m * r23));
          }
        }
        bar_sync(3, 128);
        if (lead) { mbar_arrive(bars + 8 * B_TOK); mbar_arrive(bars + 8 * B_XFREE); STAMP(67); }
      } else {
        float d[40];
#pragma unroll
        for (int i = 0; i < 40; i++) d[i] = 0.f;
        gemm_seg<0, 4, 4, 16384, B_WF2, B_WE2, 1, 10, 10240, B_XE>(d, sb, 10, wg * 8192, 0, 0, 0, true, lt, -1 PROF_PASS);
        if (tid2 == 0) STAMP(8);
        {
          const uint32_t hb = sb + XR + (2 * fj + wg) * 10240 + 2 * w * 1280 + g * 32 + t * 4;
#pragma unroll
          for (int j = 0; j < 10; j++) {
            const uint32_t a = hb + (j >> 1) * 256 + (((j & 1) ^ (g >> 2)) << 4);
            res[2 * j] = lds32(a); res[2 * j + 1] = lds32(a + 1280);
          }
        }
        mbar_wait(bars + 8 * B_TOK, 0);
        const float cs0 = __uint_as_float(lds32(sb + CS1S + (64 * wg + 16 * w + g) * 4)), cs1 = __uint_as_float(lds32(sb + CS1S + (64 * wg + 16 * w + g + 8) * 4));
        {
          uint32_t pk[20];
#pragma unroll
          for (int j = 0; j < 10; j++) {
            const int o = 4 * j, q = 2 * j;
            const float4 sa = lds128f(sb + TOKST + (8 * j + 2 * t) * 16), sc = lds128f(sb + TOKST + (8 * j + 2 * t + 1) * 16);
            pk[q] = pack_bf16(act(fmaf(d[o], sa.z, sa.w * cs0)), act(fmaf(d[o + 1], sc.z, sc.w * cs0)));
            pk[q + 1] = pack_bf16(act(fmaf(d[o + 2], sa.z, sa.w * cs1)), act(fmaf(d[o + 3], sc.z, sc.w * cs1)));
            d[o] = fmaf(bf_lo(res[q]), sa.x, sa.y); d[o + 1] = fmaf(bf_hi(res[q]), sc.x, sc.y);
            d[o + 2] = fmaf(bf_lo(res[q + 1]), sa.x, sa.y); d[o + 3] = fmaf(bf_hi(res[q + 1]), sc.x, sc.y);
          }
#pragma unroll
          for (int j = 0; j < 10; j += 2) {
            const int tok = 8 * (j + (m_ >> 1)) + rho, chunk = 2 * (w & 1) + (m_ & 1);
            stsm4t(stg + (w >> 1) * 5120 + tok * 64 + ((chunk ^ ((tok >> 1) & 3)) << 4), pk[2 * j], pk[2 * j + 1], pk[2 * j + 2], pk[2 * j + 3]);
          }
        }
        {
          const int tok = ((lane >> 1) & 1) + (lane & 4) + ((lane >> 2) & 2) + ((lane >> 4) << 3), chunk = 2 * (w & 1) + (lane & 1);
          if (!GELU_INREG) gelu_pass(stg + (w >> 1) * 5120 + tok * 64 + ((chunk ^ ((tok >> 1) & 3)) << 4), 1024, 5);
        }
        warp_signal(bars + 8 * (B_SG + wg), lane);
        bar_sync(1 + wg, 128);
        if (lead) { mbar_arrive(bars + 8 * B_XFREE); if (wg == 0) STAMP(61); }
        if (wg == 1) { mbar_wait(bars + 8 * B_SD, 0); mbar_wait(bars + 8 * B_SD, 1); }
        gemm_seg<1, 8, 4, 16384, B_WF2, B_WE2, 2, 5, 20480, B_XE>(d, sb, 5, 0, 2 + wg, wg ? 0x8 : 0x3, 0x1F, wg == 0, lt, -1 PROF_PASS);
        if (lead) STAMPV(12, wg);
        mbar_wait(bars + 8 * (B_SD + wg), 0);
#pragma unroll
        for (int j = 0; j < 10; j += 2) {
          uint32_t pk[4];
#pragma unroll
          for (int i = 0; i < 4; i++) {
            pk[i] = pack_bf16(d[4 * j + 2 * i], d[4 * j + 2 * i + 1]);
            res[2 * j + i] = pack_bf16(bf_lo(res[2 * j + i]) + bf_lo(pk[i]), bf_hi(res[2 * j + i]) + bf_hi(pk[i]));
          }
          const int tok = 8 * (j + (m_ >> 1)) + rho, chunk = 2 * w + (m_ & 1);
          stsm4t(stg + tok * 128 + ((chunk ^ (tok & 7)) << 4), pk[0], pk[1], pk[2], pk[3]);
        }
        warp_signal(bars + 8 * (B_SG + wg), lane);
        bar_sync(1 + wg, 128);
        if (lt < 80) {
          float s = 0.f, ss = 0.f;
          uint4 v[8];
#pragma unroll
          for (int i = 0; i < 8; i++) v[i] = lds128(stg + lt * 128 + (((i + lt) & 7) << 4));
#pragma unroll
          for (int i = 0; i < 8; i += 2) {
            const uint4 u = v[i], y = v[i + 1];
            const uint32_t a = hadd2(hadd2(hadd2(u.x, u.y), hadd2(u.z, u.w)), hadd2(hadd2(y.x, y.y), hadd2(y.z, y.w)));
            const uint32_t q = hadd2(hfma2(u.w, u.w, hfma2(u.z, u.z, hfma2(u.y, u.y, hmul2(u.x, u.x)))), hfma2(y.w, y.w, hfma2(y.z, y.z, hfma2(y.y, y.y, hmul2(y.x, y.x)))));
            s += bf_lo(a) + bf_hi(a); ss += bf_lo(q) + bf_hi(q);
          }
          sts64f(sb + XST + wg * 640 + lt * 8, s, ss);
        }
        warp_signal(bars + 8 * (B_SS + wg), lane);
      }
      mbar_wait(bars + 8 * (B_XE + 4), 0);
      if (warp == 8) {
        if (lane < 8) {
#pragma unroll
          for (int s = 0; s < 5; s++) sts128(sb + XR + s * 19456 + TT3 * 128 + lane * 16, 0x3F803F80u, 0x3F803F80u, 0x3F803F80u, 0x3F803F80u);
        }
        warp_signal(bars + 8 * B_ONES, lane);
      }
      if (b < 126) {
        float d[76];
#pragma unroll
        for (int i = 0; i < 76; i++) d[i] = 0.f;
        mbar_wait(bars + 8 * B_ONES, 0);
        gemm_seg<2, 4, 3, 24576, B_WF3, B_WE3, 1, 5, 19456, B_X3E>(d, sb, 5, wg * 8192, 0, 0, 0, true, lt, -1 PROF_PASS);
        if (tid == 0) STAMP(75);
        if (wg == 0) bar_sync(7, 384); else bar_arrive(7, 384);
        if (wg > 0) bar_sync(4 + wg, 256);
        if (!BATCH3 || wg == 0) {
          gemm_seg<2, 4, 9, 8192, B_WF1, B_WE1, 1, 5, 19456, B_X3E>(d, sb, 5, 0, wg == 0 ? 6 : wg == 1 ? 2 : 7, wg == 0 ? 0 : wg == 1 ? 0x40 : 0x187, 0x1F, wg == 0, lt, wg < 2 ? 5 + wg : -1 PROF_PASS);
        } else {
          const uint32_t s0 = wg == 1 ? 2 : 7, s2 = wg == 1 ? 4 : 0;
          const uint64_t la0 = mkdesc(sb + WR + s0 * 8192, 1024, 0x40000040), la2 = mkdesc(sb + WR + s2 * 8192, 1024, 0x40000040), lb = mkdesc(sb + XR, 16, 0x40000040);
          const uint32_t w0 = bars + 8 * (B_WF1 + s0), w2 = bars + 8 * (B_WF1 + s2);
          mbar_wait2(w0, wg - 1, w0 + 8, wg - 1);
          mbar_wait2(w2, wg - 1, w2 + 8, wg - 1);
          reg_fence(d);
          WG_FENCE();
#pragma unroll
          for (int c = 0; c < 5; c++) {
            if (c == 4) mbar_wait(w2 + 16, 1);
#pragma unroll
            for (int k = 0; k < 4; k++) wg_ss152k(d, (c < 2 ? la0 + c * 512 : la2 + (c - 2) * 512) + k * 128, lb + c * 1216 + k * 2);
          }
          WG_COMMIT();
          if (wg == 1) bar_arrive(6, 256);
          WG_WAIT(0);
          reg_fence(d);
          if (lt < 10) mbar_arrive(lt < 5 ? bars + 8 * (B_X3E + lt) : (lt < 7 ? w0 + 8 * (lt - 5) : w2 + 8 * (lt - 7)) + 8 * (B_WE1 - B_WF1));
        }
        if (lead) STAMPV(16, wg);
        mbar_wait(bars + 8 * B_ST3, 0);
        const float cs0 = __shfl_sync(0xffffffffu, d[73], lane | 3), cs1 = __shfl_sync(0xffffffffu, d[75], lane | 3);
        {
          uint32_t pk[38];
#pragma unroll
          for (int j = 0; j < 19; j++) {
            const float4 sa = lds128f(sb + ST3 + (8 * j + 2 * t) * 8);
            const int o = 4 * j;
            pk[2 * j] = pack_bf16(act(fmaf(d[o], sa.x, sa.y * cs0)), act(fmaf(d[o + 1], sa.z, sa.w * cs0)));
            pk[2 * j + 1] = pack_bf16(act(fmaf(d[o + 2], sa.x, sa.y * cs1)), act(fmaf(d[o + 3], sa.z, sa.w * cs1)));
          }
          if (lead) STAMPV(70, wg);
          mbar_wait(bars + 8 * (B_SD + (wg & 1)), wg == 2 ? 0 : 1);
#pragma unroll
          for (int j = 0; j < 19; j += 2) {
            const int tok = 8 * (j + (m_ >> 1)) + rho, chunk = 2 * w + (m_ & 1);
            const uint32_t a = stg + tok * 128 + ((chunk ^ (tok & 7)) << 4);
            if (j + 1 < 19) stsm4t(a, pk[2 * j], pk[2 * j + 1], pk[2 * j + 2], pk[2 * j + 3]); else stsm2t(a, pk[2 * j], pk[2 * j + 1]);
          }
        }
        {
          const int tok = (lane & 6) + ((lane >> 3) & 1) + ((lane >> 4) << 3), chunk = 2 * w + (lane & 1);
          if (!GELU_INREG) gelu_pass(stg + tok * 128 + ((chunk ^ (tok & 7)) << 4), 2048, tok < 8 ? 10 : 9);
        }
        if (lead) STAMPV(77, wg);
        warp_signal(bars + 8 * (B_SG + wg), lane);
        if (lead) STAMPV(64, wg);
      }
      if (wg < 2) {
        float d[40];
#pragma unroll
        for (int j = 0; j < 20; j++) { d[2 * j] = bf_lo(res[j]); d[2 * j + 1] = bf_hi(res[j]); }
        gemm_seg<3, 4, 6, 16384, B_WF4, B_WE4, 1, 6, 10240, B_XE>(d, sb, 27, wg * 8192 - 32768, 4, 0, 0, false, lt, -1 PROF_PASS);
        if (tid2 == 0) STAMP(47);
        if (b < 126) mbar_wait(bars + 8 * (B_SD + (wg ? 1 : 2)), 0); else mbar_wait(bars + 8 * (B_SD + wg), 1);
#pragma unroll
        for (int j = 0; j < 10; j += 2) {
          const int tok = 8 * (j + (m_ >> 1)) + rho, chunk = 2 * w + (m_ & 1);
          stsm4t(stg + tok * 128 + ((chunk ^ (tok & 7)) << 4), pack_bf16(d[4 * j], d[4 * j + 1]), pack_bf16(d[4 * j + 2], d[4 * j + 3]),
                 pack_bf16(d[4 * j + 4], d[4 * j + 5]), pack_bf16(d[4 * j + 6], d[4 * j + 7]));
        }
        warp_signal(bars + 8 * (B_SG + wg), lane);
      }
    }
    PROF_END();
  }
}

typedef CUresult (*EncFn)(CUtensorMap*, CUtensorMapDataType, cuuint32_t, void*, const cuuint64_t*, const cuuint64_t*, const cuuint32_t*,
                          const cuuint32_t*, CUtensorMapInterleave, CUtensorMapSwizzle, CUtensorMapL2promotion, CUtensorMapFloatOOBfill);

void make2d(EncFn enc, CUtensorMap* tm, const void* ptr, uint64_t inner, uint64_t outer, uint32_t bi, uint32_t bo, CUtensorMapSwizzle sw) {
  cuuint64_t gd[2] = {inner, outer};
  cuuint64_t gs[1] = {inner * 2};
  cuuint32_t bd[2] = {bi, bo}, es[2] = {1, 1};
  CUresult rr = enc(tm, CU_TENSOR_MAP_DATA_TYPE_BFLOAT16, 2, const_cast<void*>(ptr), gd, gs, bd, es, CU_TENSOR_MAP_INTERLEAVE_NONE, sw,
      CU_TENSOR_MAP_L2_PROMOTION_L2_128B, CU_TENSOR_MAP_FLOAT_OOB_FILL_NONE);
  (void)rr;
}

void make3w(EncFn enc, CUtensorMap* tm, const void* ptr, uint64_t cols, uint64_t rows, uint32_t nb, uint32_t br = 64) {
  cuuint64_t gd[3] = {64, rows, cols / 64};
  cuuint64_t gs[2] = {cols * 2, 128};
  cuuint32_t bd[3] = {64, br, nb}, es[3] = {1, 1, 1};
  enc(tm, CU_TENSOR_MAP_DATA_TYPE_BFLOAT16, 3, const_cast<void*>(ptr), gd, gs, bd, es, CU_TENSOR_MAP_INTERLEAVE_NONE, CU_TENSOR_MAP_SWIZZLE_128B,
      CU_TENSOR_MAP_L2_PROMOTION_L2_128B, CU_TENSOR_MAP_FLOAT_OOB_FILL_NONE);
}

}

extern "C" void kernel_launch(void* const* d_in, const int* in_sizes, int n_in, void* d_out, int out_size) {
  (void)in_sizes; (void)n_in; (void)out_size;
  static EncFn enc = nullptr;
  static void *kvT, *qc, *hT, *hs, *x1, *H, *st;
  if (!enc) {
    void* fn = nullptr;
    cudaDriverEntryPointQueryResult qr;
    cudaGetDriverEntryPoint("cuTensorMapEncodeTiled", &fn, cudaEnableDefault, &qr);
    enc = (EncFn)fn;
    cudaFuncSetAttribute(fused_kernel, cudaFuncAttributeMaxDynamicSharedMemorySize, SMEM_BYTES);
    cudaGetSymbolAddress(&kvT, g_kvT); cudaGetSymbolAddress(&qc, g_qc); cudaGetSymbolAddress(&hT, g_hT);
    cudaGetSymbolAddress(&hs, g_hs); cudaGetSymbolAddress(&x1, g_x1); cudaGetSymbolAddress(&H, g_H); cudaGetSymbolAddress(&st, g_st);
  }
  Params p;
  p.shift_k = (const __nv_bfloat16*)d_in[3]; p.ssm_k = (const __nv_bfloat16*)d_in[4]; p.ssm_D = (const __nv_bfloat16*)d_in[5];
  p.pw1 = (const __nv_bfloat16*)d_in[7]; p.pw2 = (const __nv_bfloat16*)d_in[8]; p.pw3 = (const __nv_bfloat16*)d_in[9]; p.pw4 = (const __nv_bfloat16*)d_in[10];
  for (int i = 0; i < 3; i++) {
    cuuint64_t gd[3] = {64, S_, 10};
    cuuint64_t gs[2] = {D_ * 2, 128};
    cuuint32_t bd[3] = {64, i == 1 ? 19u : 16u, i == 0 ? 10u : 2u}, es[3] = {1, 1, 1};
    enc(i == 0 ? &p.xin : i == 1 ? &p.kin : &p.vin, CU_TENSOR_MAP_DATA_TYPE_BFLOAT16, 3, d_in[i], gd, gs, bd, es, CU_TENSOR_MAP_INTERLEAVE_NONE,
        CU_TENSOR_MAP_SWIZZLE_128B, CU_TENSOR_MAP_L2_PROMOTION_L2_128B, CU_TENSOR_MAP_FLOAT_OOB_FILL_NONE);
  }
  make3w(enc, &p.w1p, p.pw1, D_, D_, 2);
  make3w(enc, &p.w3t, p.pw3, F_, D_, 3);
  make3w(enc, &p.w4p, p.pw4, D_, F_, 2);
  make2d(enc, &p.w2d, p.pw2, D_, D_, 64, 128, CU_TENSOR_MAP_SWIZZLE_128B);
  make2d(enc, &p.w3, p.pw3, F_, D_, 64, 64, CU_TENSOR_MAP_SWIZZLE_128B);
  make2d(enc, &p.kvT, kvT, S_, D_, 16, 128, CU_TENSOR_MAP_SWIZZLE_32B);
  make2d(enc, &p.qc, qc, 2 * S_, D_, 32, 128, CU_TENSOR_MAP_SWIZZLE_64B);
  {
    cuuint64_t gd[5] = {16, 8, 5, 80, 26};
    cuuint64_t gs[4] = {32, 256, 1280, 102400};
    cuuint32_t bd[5] = {16, 1, 5, 1, 26}, es[5] = {1, 1, 1, 1, 1};
    CUresult rr = enc(&p.hT, CU_TENSOR_MAP_DATA_TYPE_BFLOAT16, 5, hT, gd, gs, bd, es, CU_TENSOR_MAP_INTERLEAVE_NONE, CU_TENSOR_MAP_SWIZZLE_NONE,
        CU_TENSOR_MAP_L2_PROMOTION_NONE, CU_TENSOR_MAP_FLOAT_OOB_FILL_NONE);
    (void)rr;
  }
  {
    cuuint64_t gd[2] = {2176, 10};
    cuuint64_t gs[1] = {2176 * 8};
    cuuint32_t bd[2] = {154, 10}, es[2] = {1, 1};
    enc(&p.stL, CU_TENSOR_MAP_DATA_TYPE_UINT64, 2, st, gd, gs, bd, es, CU_TENSOR_MAP_INTERLEAVE_NONE, CU_TENSOR_MAP_SWIZZLE_NONE,
        CU_TENSOR_MAP_L2_PROMOTION_NONE, CU_TENSOR_MAP_FLOAT_OOB_FILL_NONE);
  }
  make2d(enc, &p.hsS, hs, D_, S_ + 2, 32, TT, CU_TENSOR_MAP_SWIZZLE_64B);
  make3w(enc, &p.hsL, (__nv_bfloat16*)hs + 2 * D_, D_, S_, 2, TT);
  make2d(enc, &p.x1S, x1, D_, S_, 64, TT, CU_TENSOR_MAP_SWIZZLE_128B);
  make2d(enc, &p.x1L, x1, D_, S_, 64, TT3, CU_TENSOR_MAP_SWIZZLE_128B);
  make2d(enc, &p.HS, H, F_, S_, 64, TT3, CU_TENSOR_MAP_SWIZZLE_128B);
  make2d(enc, &p.HL, H, F_, S_, 64, TT, CU_TENSOR_MAP_SWIZZLE_128B);
  make2d(enc, &p.outS, d_out, D_, S_, 64, TT, CU_TENSOR_MAP_SWIZZLE_128B);
  fused_kernel<<<NCTA, NTHR, SMEM_BYTES, cudaStreamPerThread>>>(p);
}
```

```cpp
#include <cuda_runtime.h>
#include <cuda_bf16.h>
#include <cuda.h>
#include <stdint.h>

namespace {

constexpr int S_ = 2048, D_ = 640, F_ = 1728;
constexpr int NCTA = 132;
constexpr int NTHR = 512;
constexpr int TT = 80;
constexpr int TT3 = 151;
constexpr float EPS = 1e-5f;

constexpr uint32_t XR = 0;
constexpr uint32_t WR = 102400;
constexpr uint32_t CR = 176128;
constexpr uint32_t TAB_E = 3 * 4, TAB_O = 1044 * 4;
__host__ __device__ constexpr uint32_t QCB(int r) { return r < 4 ? 20992 * r : CR + 36864; }
__host__ __device__ constexpr uint32_t TABB(int r) { return 20992 * r + (r < 4 ? 8192 : 0); }
__host__ __device__ constexpr uint32_t UB(int r) { return TABB(r) + 8320; }
constexpr uint32_t PK = WR;
constexpr uint32_t PX = WR + 5 * 9216;
constexpr uint32_t PSK = PX + 20480;
constexpr uint32_t EXCH = CR;
constexpr uint32_t GST = CR;
constexpr uint32_t STRAW = CR + 29696;
constexpr uint32_t MISC = CR + 45056;
constexpr uint32_t BARS = MISC;
constexpr uint32_t ROWST = MISC + 4096;
constexpr uint32_t TOKST = MISC + 1024;
constexpr uint32_t CS1S = MISC + 2304;
constexpr uint32_t ST3 = MISC + 2816;
constexpr uint32_t XST = MISC + 4864;
constexpr uint32_t SMEM_BYTES = 232448;
enum { B_X = 0, B_KV = 1  , B_F = 6  , B_U = 11  , B_QC = 16  , B_TAB = 21  , B_PST = 26  ,
       B_HST = 31  , B_HDONE = 36  , B_ONES = 41, B_CS, B_TOK, B_ST3, B_XFREE,
       B_SG = 47  , B_SD = 50  , B_SS = 53  ,
       B_WF1 = 55  , B_WE1 = 64  , B_WF2 = 73  , B_WE2 = 77  , B_WF3 = 81  , B_WE3 = 84  ,
       B_XF = 87  , B_SS3 = 92  , B_XE = 97  , B_X3E = 107  , B_WF4 = 112  , B_WE4 = 118  , B_STRAW = 124, B_SS2 = 125  , B_NUM = 128 };
enum { F_P = 0, F_C = 5  , F_1 = 10  , F_2 = 36  , F_S = 88  , F_3 = 114  , F_NUM = 117 };

struct Params {
  CUtensorMap w1p, w2d, w3t, w3, w4p, kvT, qc, hT, hsS, hsS2, hsL, x1S, x1L, HS, HL, outS, kin, vin, xin, stL;
  const __nv_bfloat16 *shift_k, *ssm_k, *ssm_D, *pw1, *pw2, *pw3, *pw4;
};

}

__device__ __align__(1024) __nv_bfloat16 g_kvT[D_ * S_];
__device__ __align__(1024) __nv_bfloat16 g_qc[D_ * S_ * 2];
__device__ __align__(1024) __nv_bfloat16 g_hT[26 * D_ * TT];
__device__ __align__(1024) __nv_bfloat16 g_hs[(S_ + 2) * D_];
__device__ __align__(1024) __nv_bfloat16 g_x1[S_ * D_];
__device__ __align__(1024) __nv_bfloat16 g_H[S_ * F_];
__device__ __align__(1024) float2 g_st[10 * 2176];
__device__ __align__(1024) float g_cs1[4 * D_];
__device__ __align__(1024) unsigned g_flag[F_NUM * 32];
__device__ unsigned g_epoch;

namespace {

__device__ __forceinline__ void mbar_init(uint32_t b, uint32_t c) { asm volatile("mbarrier.init.shared::cta.b64 [%0], %1;" ::"r"(b), "r"(c)); }
__device__ __forceinline__ void mbar_expect(uint32_t b, uint32_t bytes) {
  asm volatile("mbarrier.arrive.expect_tx.shared::cta.b64 _, [%0], %1;" ::"r"(b), "r"(bytes) : "memory");
}
__device__ __forceinline__ void mbar_arrive(uint32_t b) { asm volatile("mbarrier.arrive.shared::cta.b64 _, [%0];" ::"r"(b) : "memory"); }
__device__ __forceinline__ void mbar_wait(uint32_t b, uint32_t par) {
  asm volatile(
      "{.reg .pred p; .reg .u32 c; mov.u32 c, 0;\n"
      "WL: mbarrier.try_wait.parity.shared::cta.b64 p, [%0], %1;\n"
      "@p bra.uni WD;\n"
      "add.u32 c, c, 1; setp.lt.u32 p, c, 4000000; @p bra.uni WL; trap;\n"
      "WD: }" ::"r"(b), "r"(par) : "memory");
}
__device__ __forceinline__ void mbar_wait2(uint32_t b0, uint32_t p0, uint32_t b1, uint32_t p1) {
  asm volatile(
      "{.reg .pred p, q; .reg .u32 c; mov.u32 c, 0;\n"
      "WL: mbarrier.try_wait.parity.shared::cta.b64 p, [%0], %1;\n"
      "mbarrier.try_wait.parity.shared::cta.b64 q, [%2], %3;\n"
      "and.pred p, p, q;\n"
      "@p bra.uni WD;\n"
      "add.u32 c, c, 1; setp.lt.u32 p, c, 4000000; @p bra.uni WL; trap;\n"
      "WD: }" ::"r"(b0), "r"(p0), "r"(b1), "r"(p1) : "memory");
}
__device__ __forceinline__ void poll3(const unsigned* f0, const unsigned* f1, const unsigned* f2, unsigned target) {
  asm volatile(
      "{.reg .pred p; .reg .u32 a, b, c, n; mov.u32 n, 0;\n"
      "PL: ld.relaxed.gpu.global.u32 a, [%0]; ld.relaxed.gpu.global.u32 b, [%1]; ld.relaxed.gpu.global.u32 c, [%2];\n"
      "sub.u32 a, a, %3; sub.u32 b, b, %3; sub.u32 c, c, %3; or.b32 a, a, b; or.b32 a, a, c; setp.ge.s32 p, a, 0;\n"
      "@p bra.uni PD;\n"
      "add.u32 n, n, 1; setp.lt.u32 p, n, 4000000; @p bra.uni PL; trap;\n"
      "PD: }" ::"l"(f0), "l"(f1), "l"(f2), "r"(target) : "memory");
}
__device__ __forceinline__ void poll1(const unsigned* f, unsigned target) {
  asm volatile(
      "{.reg .pred p; .reg .u32 a, n; mov.u32 n, 0;\n"
      "PL: ld.relaxed.gpu.global.u32 a, [%0]; sub.u32 a, a, %1; setp.ge.s32 p, a, 0;\n"
      "@p bra.uni PD;\n"
      "add.u32 n, n, 1; setp.lt.u32 p, n, 4000000; @p bra.uni PL; trap;\n"
      "PD: }" ::"l"(f), "r"(target) : "memory");
}
__device__ __forceinline__ bool elect() {
  uint32_t p;
  asm volatile("{.reg .pred q; elect.sync _|q, 0xffffffff; selp.u32 %0,1,0,q;}" : "=r"(p));
  return p;
}
__device__ __forceinline__ void flag_add(unsigned* f) { asm volatile("red.relaxed.gpu.global.add.u32 [%0], 1;" ::"l"(f) : "memory"); }
__device__ __forceinline__ void tma_load3(uint32_t dst, const CUtensorMap* tm, int c0, int c1, int c2, uint32_t bar) {
  asm volatile("cp.async.bulk.tensor.3d.shared::cluster.global.mbarrier::complete_tx::bytes [%0], [%1, {%3,%4,%5}], [%2];" ::"r"(dst), "l"(tm), "r"(bar), "r"(c0), "r"(c1), "r"(c2) : "memory");
}
__device__ __forceinline__ void bulk_store(void* dst, uint32_t src, uint32_t bytes) {
  asm volatile("cp.async.bulk.global.shared::cta.bulk_group [%0], [%1], %2;" ::"l"(dst), "r"(src), "r"(bytes) : "memory");
}
__device__ __forceinline__ uint32_t swz128(uint32_t a) { return a ^ ((a >> 3) & 0x70u); }
__device__ __forceinline__ void bulk_load(uint32_t dst, const void* src, uint32_t bytes, uint32_t bar) {
  asm volatile("cp.async.bulk.shared::cluster.global.mbarrier::complete_tx::bytes [%0], [%1], %2, [%3];" ::"r"(dst), "l"(src), "r"(bytes), "r"(bar) : "memory");
}
__device__ __forceinline__ void tma_load2(uint32_t dst, const CUtensorMap* tm, int c0, int c1, uint32_t bar) {
  asm volatile("cp.async.bulk.tensor.2d.shared::cluster.global.mbarrier::complete_tx::bytes [%0], [%1, {%3,%4}], [%2];" ::"r"(dst), "l"(tm), "r"(bar), "r"(c0), "r"(c1) : "memory");
}
__device__ __forceinline__ void tma_store2(const CUtensorMap* tm, int c0, int c1, uint32_t src) {
  asm volatile("cp.async.bulk.tensor.2d.global.shared::cta.bulk_group [%0, {%2,%3}], [%1];" ::"l"(tm), "r"(src), "r"(c0), "r"(c1) : "memory");
}
__device__ __forceinline__ void tma_store5(const CUtensorMap* tm, int c0, int c1, int c2, int c3, int c4, uint32_t src) {
  asm volatile("cp.async.bulk.tensor.5d.global.shared::cta.bulk_group [%0, {%2,%3,%4,%5,%6}], [%1];" ::"l"(tm), "r"(src), "r"(c0), "r"(c1), "r"(c2), "r"(c3), "r"(c4) : "memory");
}
__device__ __forceinline__ void store_commit_wait() {
  asm volatile("cp.async.bulk.commit_group;" ::: "memory");
  asm volatile("cp.async.bulk.wait_group 0;" ::: "memory");
}
__device__ __forceinline__ void flag_release(unsigned* f) {
  asm volatile("fence.release.gpu;" ::: "memory");
  flag_add(f);
}
__device__ __forceinline__ void l2_prefetch(const void* p, uint32_t bytes) { asm volatile("cp.async.bulk.prefetch.L2.global [%0], %1;" ::"l"(p), "r"(bytes) : "memory"); }
__device__ __forceinline__ void fence_async_smem() { asm volatile("fence.proxy.async.shared::cta;" ::: "memory"); }
__device__ __forceinline__ void bar_sync(int id, int n) { asm volatile("bar.sync %0, %1;" ::"r"(id), "r"(n) : "memory"); }
__device__ __forceinline__ void bar_arrive(int id, int n) { asm volatile("bar.arrive %0, %1;" ::"r"(id), "r"(n) : "memory"); }
__device__ __forceinline__ uint32_t lds32(uint32_t a) { uint32_t v; asm volatile("ld.shared.b32 %0, [%1];" : "=r"(v) : "r"(a) : "memory"); return v; }
__device__ __forceinline__ float2 lds64f(uint32_t a) { float2 v; asm volatile("ld.shared.v2.f32 {%0,%1}, [%2];" : "=f"(v.x), "=f"(v.y) : "r"(a) : "memory"); return v; }
__device__ __forceinline__ uint4 lds128(uint32_t a) { uint4 v; asm volatile("ld.shared.v4.b32 {%0,%1,%2,%3}, [%4];" : "=r"(v.x), "=r"(v.y), "=r"(v.z), "=r"(v.w) : "r"(a) : "memory"); return v; }
__device__ __forceinline__ float4 lds128f(uint32_t a) { float4 v; asm volatile("ld.shared.v4.f32 {%0,%1,%2,%3}, [%4];" : "=f"(v.x), "=f"(v.y), "=f"(v.z), "=f"(v.w) : "r"(a) : "memory"); return v; }
__device__ __forceinline__ void sts32(uint32_t a, uint32_t v) { asm volatile("st.shared.b32 [%0], %1;" ::"r"(a), "r"(v) : "memory"); }
__device__ __forceinline__ void sts64f(uint32_t a, float x, float y) { asm volatile("st.shared.v2.f32 [%0], {%1,%2};" ::"r"(a), "f"(x), "f"(y) : "memory"); }
__device__ __forceinline__ void sts128(uint32_t a, uint32_t x, uint32_t y, uint32_t z, uint32_t w) {
  asm volatile("st.shared.v4.b32 [%0], {%1,%2,%3,%4};" ::"r"(a), "r"(x), "r"(y), "r"(z), "r"(w) : "memory");
}
__device__ __forceinline__ void ldsm4(uint32_t (&r)[4], uint32_t a) {
  asm volatile("ldmatrix.sync.aligned.m8n8.x4.shared.b16 {%0,%1,%2,%3}, [%4];" : "=r"(r[0]), "=r"(r[1]), "=r"(r[2]), "=r"(r[3]) : "r"(a) : "memory");
}
__device__ __forceinline__ void stsm4t(uint32_t a, uint32_t r0, uint32_t r1, uint32_t r2, uint32_t r3) {
  asm volatile("stmatrix.sync.aligned.m8n8.x4.trans.shared.b16 [%0], {%1,%2,%3,%4};" ::"r"(a), "r"(r0), "r"(r1), "r"(r2), "r"(r3) : "memory");
}
__device__ __forceinline__ void stsm2t(uint32_t a, uint32_t r0, uint32_t r1) {
  asm volatile("stmatrix.sync.aligned.m8n8.x2.trans.shared.b16 [%0], {%1,%2};" ::"r"(a), "r"(r0), "r"(r1) : "memory");
}
__device__ __forceinline__ uint32_t pack_bf16(float lo, float hi) { uint32_t r; asm("cvt.rn.bf16x2.f32 %0, %1, %2;" : "=r"(r) : "f"(hi), "f"(lo)); return r; }
__device__ __forceinline__ float bf_lo(uint32_t v) { return __uint_as_float(v << 16); }
__device__ __forceinline__ float bf_hi(uint32_t v) { return __uint_as_float(v & 0xffff0000u); }
__device__ __forceinline__ uint32_t hfma2(uint32_t a, uint32_t b, uint32_t c) { uint32_t r; asm("fma.rn.bf16x2 %0, %1, %2, %3;" : "=r"(r) : "r"(a), "r"(b), "r"(c)); return r; }
__device__ __forceinline__ uint32_t hmul2(uint32_t a, uint32_t b) { uint32_t r; asm("mul.bf16x2 %0, %1, %2;" : "=r"(r) : "r"(a), "r"(b)); return r; }
__device__ __forceinline__ float gelu_half(float hz) {
  float u = hz * fmaf(hz * hz, 8.f * 0.044715f * 0.7978845608028654f, 2.f * 0.7978845608028654f);
  float t;
  asm("tanh.approx.f32 %0, %1;" : "=f"(t) : "f"(u));
  return fmaf(hz, t, hz);
}
__device__ __forceinline__ uint32_t gelu_pair(float hlo, float hhi) { return pack_bf16(gelu_half(hlo), gelu_half(hhi)); }
__device__ __forceinline__ uint64_t mkdesc(uint32_t addr, uint32_t lbo, uint32_t hi) { return (uint64_t)((addr >> 4) | ((lbo >> 4) << 16)) | ((uint64_t)hi << 32); }
#define WG_FENCE() asm volatile("wgmma.fence.sync.aligned;" ::: "memory")
#define WG_COMMIT() asm volatile("wgmma.commit_group.sync.aligned;" ::: "memory")
#define WG_WAIT(n) asm volatile("wgmma.wait_group.sync.aligned %0;" ::"n"(n) : "memory")
template <int N> __device__ __forceinline__ void reg_fence(float (&d)[N]) {
#pragma unroll
  for (int i = 0; i < N; i++) asm volatile("" : "+f"(d[i])::"memory");
}

__device__ __forceinline__ void wg_ss80n(float (&d)[40], uint64_t da, uint64_t db){
  asm volatile("wgmma.mma_async.sync.aligned.m64n80k16.f32.bf16.bf16 {%0,%1,%2,%3,%4,%5,%6,%7,%8,%9,%10,%11,%12,%13,%14,%15,%16,%17,%18,%19,%20,%21,%22,%23,%24,%25,%26,%27,%28,%29,%30,%31,%32,%33,%34,%35,%36,%37,%38,%39}, %40, %41, 1, 1, 1, 1, 1;"
   : "+f"(d[0]),"+f"(d[1]),"+f"(d[2]),"+f"(d[3]),"+f"(d[4]),"+f"(d[5]),"+f"(d[6]),"+f"(d[7]),"+f"(d[8]),"+f"(d[9]),"+f"(d[10]),"+f"(d[11]),"+f"(d[12]),"+f"(d[13]),"+f"(d[14]),"+f"(d[15]),"+f"(d[16]),"+f"(d[17]),"+f"(d[18]),"+f"(d[19]),"+f"(d[20]),"+f"(d[21]),"+f"(d[22]),"+f"(d[23]),"+f"(d[24]),"+f"(d[25]),"+f"(d[26]),"+f"(d[27]),"+f"(d[28]),"+f"(d[29]),"+f"(d[30]),"+f"(d[31]),"+f"(d[32]),"+f"(d[33]),"+f"(d[34]),"+f"(d[35]),"+f"(d[36]),"+f"(d[37]),"+f"(d[38]),"+f"(d[39])
   : "l"(da), "l"(db));
}
__device__ __forceinline__ void wg_ss80k(float (&d)[40], uint64_t da, uint64_t db){
  asm volatile("wgmma.mma_async.sync.aligned.m64n80k16.f32.bf16.bf16 {%0,%1,%2,%3,%4,%5,%6,%7,%8,%9,%10,%11,%12,%13,%14,%15,%16,%17,%18,%19,%20,%21,%22,%23,%24,%25,%26,%27,%28,%29,%30,%31,%32,%33,%34,%35,%36,%37,%38,%39}, %40, %41, 1, 1, 1, 1, 0;"
   : "+f"(d[0]),"+f"(d[1]),"+f"(d[2]),"+f"(d[3]),"+f"(d[4]),"+f"(d[5]),"+f"(d[6]),"+f"(d[7]),"+f"(d[8]),"+f"(d[9]),"+f"(d[10]),"+f"(d[11]),"+f"(d[12]),"+f"(d[13]),"+f"(d[14]),"+f"(d[15]),"+f"(d[16]),"+f"(d[17]),"+f"(d[18]),"+f"(d[19]),"+f"(d[20]),"+f"(d[21]),"+f"(d[22]),"+f"(d[23]),"+f"(d[24]),"+f"(d[25]),"+f"(d[26]),"+f"(d[27]),"+f"(d[28]),"+f"(d[29]),"+f"(d[30]),"+f"(d[31]),"+f"(d[32]),"+f"(d[33]),"+f"(d[34]),"+f"(d[35]),"+f"(d[36]),"+f"(d[37]),"+f"(d[38]),"+f"(d[39])
   : "l"(da), "l"(db));
}
__device__ __forceinline__ void wg_ss152k(float (&d)[76], uint64_t da, uint64_t db){
  asm volatile("wgmma.mma_async.sync.aligned.m64n152k16.f32.bf16.bf16 {%0,%1,%2,%3,%4,%5,%6,%7,%8,%9,%10,%11,%12,%13,%14,%15,%16,%17,%18,%19,%20,%21,%22,%23,%24,%25,%26,%27,%28,%29,%30,%31,%32,%33,%34,%35,%36,%37,%38,%39,%40,%41,%42,%43,%44,%45,%46,%47,%48,%49,%50,%51,%52,%53,%54,%55,%56,%57,%58,%59,%60,%61,%62,%63,%64,%65,%66,%67,%68,%69,%70,%71,%72,%73,%74,%75}, %76, %77, 1, 1, 1, 1, 0;"
   : "+f"(d[0]),"+f"(d[1]),"+f"(d[2]),"+f"(d[3]),"+f"(d[4]),"+f"(d[5]),"+f"(d[6]),"+f"(d[7]),"+f"(d[8]),"+f"(d[9]),"+f"(d[10]),"+f"(d[11]),"+f"(d[12]),"+f"(d[13]),"+f"(d[14]),"+f"(d[15]),"+f"(d[16]),"+f"(d[17]),"+f"(d[18]),"+f"(d[19]),"+f"(d[20]),"+f"(d[21]),"+f"(d[22]),"+f"(d[23]),"+f"(d[24]),"+f"(d[25]),"+f"(d[26]),"+f"(d[27]),"+f"(d[28]),"+f"(d[29]),"+f"(d[30]),"+f"(d[31]),"+f"(d[32]),"+f"(d[33]),"+f"(d[34]),"+f"(d[35]),"+f"(d[36]),"+f"(d[37]),"+f"(d[38]),"+f"(d[39]),"+f"(d[40]),"+f"(d[41]),"+f"(d[42]),"+f"(d[43]),"+f"(d[44]),"+f"(d[45]),"+f"(d[46]),"+f"(d[47]),"+f"(d[48]),"+f"(d[49]),"+f"(d[50]),"+f"(d[51]),"+f"(d[52]),"+f"(d[53]),"+f"(d[54]),"+f"(d[55]),"+f"(d[56]),"+f"(d[57]),"+f"(d[58]),"+f"(d[59]),"+f"(d[60]),"+f"(d[61]),"+f"(d[62]),"+f"(d[63]),"+f"(d[64]),"+f"(d[65]),"+f"(d[66]),"+f"(d[67]),"+f"(d[68]),"+f"(d[69]),"+f"(d[70]),"+f"(d[71]),"+f"(d[72]),"+f"(d[73]),"+f"(d[74]),"+f"(d[75])
   : "l"(da), "l"(db));
}
__device__ __forceinline__ void wg_rs64(float (&d)[32], const uint32_t (&a)[4], uint64_t db, int sd){
  asm volatile("{.reg .pred p; setp.ne.b32 p, %37, 0;\n"
   "wgmma.mma_async.sync.aligned.m64n64k16.f32.bf16.bf16 {%0,%1,%2,%3,%4,%5,%6,%7,%8,%9,%10,%11,%12,%13,%14,%15,%16,%17,%18,%19,%20,%21,%22,%23,%24,%25,%26,%27,%28,%29,%30,%31}, {%32,%33,%34,%35}, %36, p, 1, 1, 0;}"
   : "+f"(d[0]),"+f"(d[1]),"+f"(d[2]),"+f"(d[3]),"+f"(d[4]),"+f"(d[5]),"+f"(d[6]),"+f"(d[7]),"+f"(d[8]),"+f"(d[9]),"+f"(d[10]),"+f"(d[11]),"+f"(d[12]),"+f"(d[13]),"+f"(d[14]),"+f"(d[15]),"+f"(d[16]),"+f"(d[17]),"+f"(d[18]),"+f"(d[19]),"+f"(d[20]),"+f"(d[21]),"+f"(d[22]),"+f"(d[23]),"+f"(d[24]),"+f"(d[25]),"+f"(d[26]),"+f"(d[27]),"+f"(d[28]),"+f"(d[29]),"+f"(d[30]),"+f"(d[31])
   : "r"(a[0]),"r"(a[1]),"r"(a[2]),"r"(a[3]), "l"(db), "r"(sd));
}

template <int J, int Q0, int Q1> __device__ __forceinline__ void conv_mma(float (&d)[32], const uint32_t (&A)[16][4], uint64_t db) {
#pragma unroll
  for (int q = Q0; q <= Q1; q++)
#pragma unroll
    for (int s = 0; s < 4; s++) wg_rs64(d, A[4 * q + s], db + ((1024 * (J - q) - 32 * s) >> 4), (q | s) != 0);
}
template <int J>
__device__ __forceinline__ void conv_drain(float (&d)[32], float& c0, float& c1, uint32_t ex, uint32_t qc, uint32_t hst, int wg, int w, int lane) {
  reg_fence(d);
  float z[4] = {d[0] + c0, d[1] + c1, d[4] + d[2], d[5] + d[3]};
#pragma unroll
  for (int pp = 1; pp < 4; pp++)
    if (J < 3 || w + pp < 4)
      sts64f(ex + w * 768 + (J & 1) * 3072 + (pp - 1) * 256, __uint_as_float(pack_bf16(d[8 * pp] + d[8 * pp - 2], d[8 * pp + 1] + d[8 * pp - 1])),
             __uint_as_float(pack_bf16(d[8 * pp + 4] + d[8 * pp + 2], d[8 * pp + 5] + d[8 * pp + 3])));
  asm volatile("mov.b32 %0,%1;" : "=f"(c0) : "f"(d[30]));
  asm volatile("mov.b32 %0,%1;" : "=f"(c1) : "f"(d[31]));
  uint32_t v0[2], v1[2];
#pragma unroll
  for (int jj = 0; jj < 2; jj++) { v0[jj] = lds32(qc + (8 * J + jj) * 256); v1[jj] = lds32((qc ^ 32) + (8 * J + jj) * 256); }
  bar_sync(1 + wg, 128);
#pragma unroll
  for (int pp = 1; pp < 4; pp++) {
    const bool later = pp > w;
    if (J > 0 || !later) {
      const float2 u = lds64f(ex + ((w - pp) & 3) * 768 + (pp - 1) * 256 + (((J & 1) != 0) != later ? 3072 : 0));
      z[0] += bf_lo(__float_as_uint(u.x)); z[1] += bf_hi(__float_as_uint(u.x)); z[2] += bf_lo(__float_as_uint(u.y)); z[3] += bf_hi(__float_as_uint(u.y));
    }
  }
  const bool p = lane & 4, sw = lane & 2;
#pragma unroll
  for (int jj = 0; jj < 2; jj++) {
    const float recv = __shfl_xor_sync(0xffffffffu, p ? z[2 * jj] : z[2 * jj + 1], 4), keep = p ? z[2 * jj + 1] : z[2 * jj];
    const float ylo = p ? recv : keep, yhi = p ? keep : recv;
    const uint32_t qv = sw ? v1[jj] : v0[jj], cv = sw ? v0[jj] : v1[jj];
    sts32(hst + (8 * J + jj) * 128, pack_bf16(fmaf(bf_lo(qv), ylo, bf_lo(cv)), fmaf(bf_hi(qv), yhi, bf_hi(cv))));
  }
}
template <int I0> __device__ __forceinline__ void conv_load_a(uint32_t (&A)[16][4], uint32_t ta) {
#pragma unroll
  for (int i = I0; i < I0 + 8; i++) {
    const uint32_t a = ta - (i >> 2) * 1024 - (i & 3) * 32;
    A[i][0] = lds32(a); A[i][1] = lds32(a - 128); A[i][2] = lds32(a + 16); A[i][3] = lds32(a - 112);
  }
}

template <int KIND, int KS, int NWP, uint32_t WB, int WF, int WE, int RW, int NX, uint32_t XB, int XE, int NACC>
__device__ __forceinline__ void gemm_seg(float (&d)[NACC], uint32_t sb, int nch, uint32_t woff, uint32_t wi, uint32_t wmask, uint32_t xmask, bool waitx,
                                         int lt, int tok_arrive) {
  const uint32_t bars = sb + BARS;
  const uint64_t la0 = mkdesc(sb + WR + woff, 1024, 0x40000040), lb0 = KIND == 0 ? mkdesc(sb + XR, 256, 0xC0000050) : mkdesc(sb + XR, 16, 0x40000040);
  uint32_t xi = 0, pw = 0, px = 0;
  uint32_t bw = bars + 8 * WF + 8 * wi, bx = bars + 8 * B_XF;
  constexpr bool RX = KIND == 1 || KIND == 2;
  if (waitx) mbar_wait2(bx, xmask & 1, bw, (wmask >> wi) & 1); else mbar_wait(bw, (wmask >> wi) & 1);
  reg_fence(d);
#pragma unroll 1
  for (int c = nch; c > 0; c--) {
    const uint64_t la = la0 + wi * (WB >> 4), lb = lb0 + xi * (XB >> 4);
    WG_FENCE();
#pragma unroll
    for (int k = 0; k < KS; k++) {
      if constexpr (KIND == 0) wg_ss80n(d, la + k * 128, lb + k * 160);
      else if constexpr (KIND == 1 || KIND == 3) wg_ss80k(d, la + k * 128, lb + (k >> 2) * 640 + (k & 3) * 2);
      else wg_ss152k(d, la + k * 128, lb + k * 2);
    }
    WG_COMMIT();
    const uint32_t rw = bw + 8 * (WE - WF), rx = bx + 8 * (XE - B_XF);
    wmask ^= 1u << wi;
    wi = wi + 1 == NWP ? 0 : wi + 1;
    if (KIND == 3) xi = xi + 1 == NX ? 0 : xi + 1;
    else if (KIND != 0) { xmask ^= 1u << xi; xi = xi + 1 == NX ? 0 : xi + 1; }
    else xi++;
    bw = bars + 8 * WF + 8 * wi; bx = bars + 8 * B_XF + 8 * (KIND == 0 ? xi >> 1 : xi);
    if (KIND == 0) waitx = !(xi & 1);
    if (KIND == 0 && xi == 8) bar_sync(7, 352);
    if (c == 1 && tok_arrive >= 0) bar_arrive(tok_arrive, 256);
    WG_WAIT(1);
    if (lt < RW && pw) { mbar_arrive(pw); if (RX && lt == 0) mbar_arrive(px); }
    if (c > 1) { if (waitx) mbar_wait2(bx, (xmask >> xi) & 1, bw, (wmask >> wi) & 1); else mbar_wait(bw, (wmask >> wi) & 1); }
    pw = rw; px = rx;
  }
  WG_WAIT(0);
  reg_fence(d);
  if (lt < RW) { mbar_arrive(pw); if (RX && lt == 0) mbar_arrive(px); }
}

__device__ __forceinline__ void pre_unit(uint32_t sb, int r, int j, int lane, float2 st0, float2 st1) {
  const int m_ = lane >> 3, rho = lane & 7, t = lane & 3;
  const uint32_t col = (j & 3) * 32 + (m_ >> 1) * 16, row = (m_ & 1) * 8 + rho;
  const uint32_t ka = sb + PK + r * 9216 + ((j >> 2) * 19 + row) * 128 + col;
  uint32_t k0[4], k1[4], k2[4], k3[4], vv[4], xx[4];
  ldsm4(k3, swz128(ka)); ldsm4(k2, swz128(ka + 128)); ldsm4(k1, swz128(ka + 256)); ldsm4(k0, swz128(ka + 384));
  ldsm4(vv, swz128(sb + PK + r * 9216 + 5120 + ((j >> 2) * 16 + row) * 128 + col));
  ldsm4(xx, swz128(sb + PX + ((2 * r + (j >> 2)) * 16 + row) * 128 + col));
  uint32_t kvr[4], qr[4], cr[4];
#pragma unroll
  for (int oc = 0; oc < 2; oc++) {
    const int ch = 128 * r + 16 * j + 8 * oc + 2 * t;
    const uint4 v = lds128(sb + PSK + ch * 8);
    const uint32_t dd = lds32(sb + PSK + 5120 + ch * 2);
    const uint32_t w0 = __byte_perm(v.x, v.z, 0x5410), w1 = __byte_perm(v.x, v.z, 0x7632), w2 = __byte_perm(v.y, v.w, 0x5410), w3 = __byte_perm(v.y, v.w, 0x7632);
#pragma unroll
    for (int th = 0; th < 2; th++) {
      const int m = 2 * oc + th;
      uint32_t ks = hmul2(k3[m], w3);
      ks = hfma2(k2[m], w2, ks);
      ks = hfma2(k1[m], w1, ks);
      ks = hfma2(k0[m], w0, ks);
      kvr[m] = hmul2(ks, vv[m]);
      const float mm = th ? st1.x : st0.x, rr = th ? st1.y : st0.y;
      const float xl = bf_lo(xx[m]), xh = bf_hi(xx[m]);
      const float ql = (xl - mm) * rr, qh = (xh - mm) * rr;
      qr[m] = pack_bf16(ql, qh);
      cr[m] = pack_bf16(fmaf(ql * bf_lo(dd), bf_lo(kvr[m]), xl), fmaf(qh * bf_hi(dd), bf_hi(kvr[m]), xh));
    }
  }
  const int ch = 16 * j + 8 * (m_ >> 1) + rho, th = m_ & 1;
  stsm4t(sb + EXCH + 12288 + r * 4096 + ch * 32 + ((th ^ ((ch >> 2) & 1)) << 4), kvr[0], kvr[1], kvr[2], kvr[3]);
  const uint32_t qa = sb + QCB(r) + ch * 64;
  const int sx = (ch >> 1) & 3;
  stsm4t(qa + ((th ^ sx) << 4), qr[0], qr[1], qr[2], qr[3]);
  stsm4t(qa + (((2 + th) ^ sx) << 4), cr[0], cr[1], cr[2], cr[3]);
}
__device__ __forceinline__ void build_table(uint32_t sb, int r, int lt) {
  const uint32_t tb = sb + TABB(r), raw = sb + UB(r) + 128;
#pragma unroll
  for (int i = 0; i < 2; i++) {
    const int s = lt + 128 * i;
    const uint4 v = lds128(raw + s * 16);
    const uint32_t pv = lds32(raw + s * 16 - 4);
    sts128(tb + TAB_O + (1020 - 4 * s) * 4, __byte_perm(v.w, 0, 0x1032), __byte_perm(v.z, 0, 0x1032), __byte_perm(v.y, 0, 0x1032), __byte_perm(v.x, 0, 0x1032));
    sts128(tb + TAB_E + (1021 - 4 * s) * 4, __byte_perm(v.w, v.z, 0x7610), __byte_perm(v.z, v.y, 0x7610), __byte_perm(v.y, v.x, 0x7610), __byte_perm(v.x, pv, 0x7610));
  }
  if (lt < 7) sts32(tb + (lt < 3 ? TAB_E + (1025 + lt) * 4 : TAB_O + (1021 + lt) * 4), 0);
}
__device__ __forceinline__ void warp_signal(uint32_t bar, int lane) {
  fence_async_smem();
  __syncwarp();
  if (lane == 0) mbar_arrive(bar);
}

__device__ __forceinline__ void filter_load(const Params& p, uint32_t sb, int b, int r) {
  mbar_expect(sb + BARS + 8 * (B_F + r), 4096);
  bulk_load(sb + UB(r) + 128, p.ssm_k + (size_t)(128 * r + b) * S_, 4096, sb + BARS + 8 * (B_F + r));
}
__device__ __forceinline__ void front_load(const Params& p, uint32_t sb, int b, int r) {
  const uint32_t bars = sb + BARS;
  mbar_expect(bars + 8 * (B_KV + r), 4864 + 4096);
  tma_load3(sb + PK + r * 9216, &p.kin, 0, 16 * b - 3, 2 * r, bars + 8 * (B_KV + r));
  tma_load3(sb + PK + r * 9216 + 5120, &p.vin, 0, 16 * b, 2 * r, bars + 8 * (B_KV + r));
  if (r < 2) filter_load(p, sb, b, r);
}

__global__ void __launch_bounds__(NTHR, 1) fused_kernel(const __grid_constant__ Params p) {
  extern __shared__ __align__(1024) uint8_t smem_raw[];
  const uint32_t sb = (uint32_t)__cvta_generic_to_shared(smem_raw);
  const int tid = threadIdx.x, lane = tid & 31;
  const int warp = __shfl_sync(0xffffffffu, tid >> 5, 0);
  const int wg = warp >> 2;
  const int b = blockIdx.x;
  const uint32_t bars = sb + BARS;
  if (warp >= 12) {
    if (warp == 13 && b >= 128 && elect()) {
      mbar_init(bars + 8 * B_X, 1);
      mbar_expect(bars + 8 * B_X, 204800);
      bulk_load(sb, p.pw1 + (b - 128) * 160 * D_, 102400, bars + 8 * B_X);
      bulk_load(sb + 102400, p.pw1 + ((b - 128) * 160 + 80) * D_, 102400, bars + 8 * B_X);
    }
    if (warp < 14 && b < 128 && elect()) {
      if (warp == 13) {
        mbar_init(bars + 8 * B_X, 1);
        mbar_expect(bars + 8 * B_X, 20480 + 5120 + 1280);
        tma_load3(sb + PX, &p.xin, 0, 16 * b, 0, bars + 8 * B_X);
        bulk_load(sb + PSK, p.shift_k, 5120, bars + 8 * B_X);
        bulk_load(sb + PSK + 5120, p.ssm_D, 1280, bars + 8 * B_X);
      }
#pragma unroll 1
      for (int r = warp - 12; r < 5; r += 2) { mbar_init(bars + 8 * (B_KV + r), 1); mbar_init(bars + 8 * (B_F + r), 1); front_load(p, sb, b, r); }
    }
  } else {
    const int i = B_U + warp + 12 * lane;
    if (i < B_NUM) {
      uint32_t cnt = 1;
      if (i >= B_PST && i < B_HST) cnt = 8;
      else if ((i >= B_HST && i < B_HDONE) || (i >= B_SG && i < B_SD) || i >= B_SS2 || i == B_SS3 || i == B_SS3 + 1 || (i >= B_SS && i < B_WF1)) cnt = 4;
      else if (i == B_XFREE) cnt = 6;
      else if (i == B_TOK) cnt = 4;
      else if ( (i >= B_X3E && i < B_WF4) || (i >= B_WE3 && i < B_XF)) cnt = 3;
      else if ((i >= B_XE && i < B_X3E) || (i >= B_WE2 && i < B_WF3) || (i >= B_WF4 && i < B_STRAW)) cnt = 2;
      mbar_init(bars + 8 * i, cnt);
    }
  }
  if (tid < 40 && b < 128) sts128(sb + UB(tid >> 3) + (tid & 7) * 16, 0, 0, 0, 0);
  asm volatile("{.reg .pred p; setp.ne.u32 p, %0, 0; @p trap;}" ::"r"(sb & 1023));
  __syncthreads();

  const int ti = b / 5, fj = b % 5;
  const int t3 = (b / 3) % 14, f3 = b / 42 * 3 + b % 3;

  if (wg == 3) {
    asm volatile("setmaxnreg.dec.sync.aligned.u32 32;");
    if (b < 130) {
      if (warp == 12) {
        if (b < 128) {
          mbar_wait(bars + 8 * (B_QC + 1), 0);
          if (elect()) {
            l2_prefetch(reinterpret_cast<const uint8_t*>(p.pw1) + b * 6400, 6400);
            l2_prefetch(reinterpret_cast<const uint8_t*>(p.pw2) + b * 6400, 6400);
            l2_prefetch(reinterpret_cast<const uint8_t*>(p.pw3) + b * 17280, 17280);
            l2_prefetch(reinterpret_cast<const uint8_t*>(p.pw4) + b * 17280, 17280);
          }
          mbar_wait(bars + 8 * B_HDONE, 0);
        } else {
          mbar_wait(bars + 8 * B_CS, 0);
        }
#pragma unroll 1
        for (int n = 0; n < 20; n++) {
          const uint32_t q = n & 3;
          mbar_wait(bars + 8 * (B_WE2 + q), ((n >> 2) & 1) ^ 1);
          if (elect()) {
            mbar_expect(bars + 8 * (B_WF2 + q), 16384);
            if (n < 10) tma_load3(sb + WR + q * 16384, &p.w1p, 0, 64 * n, 2 * fj, bars + 8 * (B_WF2 + q));
            else tma_load2(sb + WR + q * 16384, &p.w2d, 128 * fj + (n < 15 ? 0 : 64), 128 * (n < 15 ? n - 10 : n - 15), bars + 8 * (B_WF2 + q));
          }
        }
        if (b < 126) {
#pragma unroll 1
          for (int i = 0; i < 5; i++) {
            const uint32_t q = i < 3 ? i : i - 3;
            mbar_wait(bars + 8 * (i < 3 ? B_WE2 + 1 + i : B_WE3 + q), 0);
            if (elect()) { mbar_expect(bars + 8 * (B_WF3 + q), 24576); tma_load3(sb + WR + q * 24576, &p.w3t, 0, 128 * i, 3 * f3, bars + 8 * (B_WF3 + q)); }
          }
          int k = 64, f = 192 * f3;
          uint32_t s = 6;
#pragma unroll 1
          for (int j = 0; j < 15; j++) {
            mbar_wait(bars + 8 * (j < 3 ? B_WE3 + 2 : j < 6 ? B_WE3 : j < 9 ? B_WE3 + 1 : B_WE1 + s), j >= 3 && j < 9);
            if (elect()) { mbar_expect(bars + 8 * (B_WF1 + s), 8192); tma_load2(sb + WR + s * 8192, &p.w3, f, k, bars + 8 * (B_WF1 + s)); }
            k += 128;
            if (k == 704) { k = 64; f += 64; }
            if (++s == 9) s = 0;
          }
        }
        {
          int k = 0;
          uint32_t q = 4, par = 1;
#pragma unroll 1
          for (int i = 0; i < 27; i++) {
            if (i >= 6) mbar_wait(bars + 8 * (B_WE4 + q), par);
            else if (b >= 126) { if (i == 0) { mbar_wait(bars + 8 * (B_WE2 + 3), 0); mbar_wait(bars + 8 * (B_XE + 4), 0); } }
            else if (i < 2 || i >= 4) mbar_wait(bars + 8 * (B_WE1 + ((0x210075u >> (4 * i)) & 15u)), i >= 1);
            else if (i == 2) mbar_wait(bars + 8 * (B_X3E + 4), 1);
            if (elect()) {
              mbar_expect(bars + 8 * (B_WF4 + q), 16384);
              tma_load3(sb + WR - 32768 + q * 16384, &p.w4p, 0, k, 2 * fj, bars + 8 * (B_WF4 + q));
            }
            k += 192;
            if (k >= F_) k -= F_ - 64;
            if (++q == 6) q = 0;
            if (q == 4) par ^= 1;
          }
        }
      } else if (warp == 13) {
        unsigned ep;
        asm volatile("ld.relaxed.gpu.global.u32 %0, [%1];" : "=r"(ep) : "l"(&g_epoch) : "memory");
        ep += 1;
        if (lane < 5) mbar_expect(bars + 8 * (B_XF + lane), 20480);
        __syncwarp();
        if (b < 128) {
          if (lane < 10) mbar_expect(bars + 8 * (B_U + lane), lane < 5 ? 4096 : 8192);
          __syncwarp();
          poll1(&g_flag[F_P * 32], ep * 128u);
          __syncwarp();
#pragma unroll 1
          for (int r = 0; r < 5; r++) {
            mbar_wait(bars + 8 * (B_TAB + r), 0);
            if (elect()) {
              const int c = 128 * r + b;
              bulk_load(sb + UB(r) + 128, g_kvT + (size_t)c * S_, 4096, bars + 8 * (B_U + r));
              bulk_load(sb + QCB(r), g_qc + (size_t)c * S_ * 2, 8192, bars + 8 * (B_QC + r));
            }
          }
        } else {
          mbar_wait(bars + 8 * B_CS, 0);
        }
#pragma unroll 1
        for (int r = 0; r < 5; r++) {
          if (b < 128) mbar_wait(bars + 8 * (B_HDONE + r), 0);
          poll1(&g_flag[(F_C + r) * 32], ep * (r == 0 ? 132u : 128u));
          if (elect()) {
            bulk_load(sb + XR + r * 20480, g_hT + (size_t)ti * (D_ * TT) + r * 10240, 20480, bars + 8 * (B_XF + r));
          }
        }
        mbar_wait(bars + 8 * B_XFREE, 0);
        if (lane < 5) mbar_expect(bars + 8 * (B_XF + lane), 20480);
        __syncwarp();
        poll3(&g_flag[(F_1 + max(ti - 1, 0)) * 32], &g_flag[(F_1 + ti) * 32], &g_flag[(F_1 + min(ti + 1, 25)) * 32], ep * 10u);
#pragma unroll 1
        for (int i = 0; i < 5; i++) {
          if (elect()) {
            tma_load3(sb + XR + i * 20480, &p.hsL, 0, TT * ti, 2 * i, bars + 8 * (B_XF + i));
          }
        }
        if (b < 126) {
          const int t0 = (TT3 * t3) / TT, t2 = min((TT3 * t3 + TT3 - 1) / TT, 25);
#pragma unroll 1
          for (int h = 0; h < 2; h++) {
            poll3(&g_flag[(F_2 + 2 * t0 + h) * 32], &g_flag[(F_2 + 2 * (t0 + 1) + h) * 32], &g_flag[(F_2 + 2 * t2 + h) * 32], ep * 5u);
            __syncwarp();
#pragma unroll 1
            for (int s = 0; s < 5; s++) {
              mbar_wait(bars + 8 * ((h ? B_X3E : B_XE) + s), 0);
              if (elect()) {
                mbar_expect(bars + 8 * (B_XF + s), TT3 * 128);
                tma_load2(sb + XR + s * 19456, &p.x1L, 128 * s + 64 * h, TT3 * t3, bars + 8 * (B_XF + s));
              }
            }
          }
        }
        {
          uint32_t s = 0, q = 4, par = 1;
          if (b >= 126) mbar_wait(bars + 8 * (B_XE + 4), 0);
#pragma unroll 1
          for (int cl = 0; cl < 3; cl++) {
            poll1(&g_flag[(F_3 + cl) * 32], ep * 126u);
            __syncwarp();
#pragma unroll 1
            for (int k = 64 * cl; k < F_; k += 192) {
              if (cl || k >= 6 * 192) mbar_wait(bars + 8 * (B_WE4 + q), par);
              else if (b < 126) mbar_wait(bars + 8 * (B_X3E + ((s + 1) >> 1)), 1);
              if (elect()) {
                mbar_expect(bars + 8 * (B_WF4 + q), 10240);
                tma_load2(sb + XR + s * 10240, &p.HL, k, TT * ti, bars + 8 * (B_WF4 + q));
              }
              if (++q == 6) q = 0;
              if (++s == 6) { s = 0; par ^= 1; }
            }
          }
        }
        if (b == 0 && lane == 0) asm volatile("st.relaxed.gpu.global.u32 [%0], %1;" ::"l"(&g_epoch), "r"(ep) : "memory");
      } else {
        const int sw = warp - 14;
        if (sw && lane < 20) asm volatile("prefetch.tensormap [%0];" ::"l"(&p.w1p + lane) : "memory");
        __syncwarp();
        if (b == 0 && warp == 14 && lane == 0) {
#pragma unroll 1
          for (int i = 0; i < 60; i++)
            reinterpret_cast<uint4*>(g_hs + (2 + (i >= 40)) * D_ + (i >= 20 ? 320 : 0))[i % 20] = make_uint4(0, 0, 0, 0);
          asm volatile("fence.proxy.async.global;" ::: "memory");
        }
        __syncwarp();
        if (b < 128) {
          if (!sw) {
#pragma unroll 1
            for (int r = 0; r < 5; r++) {
              mbar_wait(bars + 8 * (B_PST + r), 0);
              if (lane == 0) {
                tma_store2(&p.kvT, 16 * b, 128 * r, sb + EXCH + 12288 + r * 4096);
                tma_store2(&p.qc, 32 * b, 128 * r, sb + QCB(r));
              }
              __syncwarp();
            }
            if (lane == 0) {
              store_commit_wait();
              flag_release(&g_flag[F_P * 32]);
#pragma unroll 1
              for (int r = 2; r < 5; r++) filter_load(p, sb, b, r);
            }
            __syncwarp();
          }
          {
#pragma unroll 1
            for (int r = sw; r < 5; r += 2) {
              mbar_wait(bars + 8 * (B_HST + r), 0);
              if (elect()) {
                const int ch = 128 * r + b;
                tma_store5(&p.hT, 0, ch & 7, 0, ch >> 3, 0, sb + TABB(r));
                store_commit_wait();
                mbar_arrive(bars + 8 * (B_HDONE + r));
                flag_release(&g_flag[(F_C + r) * 32]);
              }
              __syncwarp();
            }
          }
        }
        const uint32_t stg = sb + GST + sw * 19456;
        const int fa = 128 * fj + 64 * sw, ga = fa / 160, gb = (fa + 32) / 160;
        const int ra = TT * ti + ((0x0413 >> (4 * ga)) & 15), rb = TT * ti + ((0x0413 >> (4 * gb)) & 15);
#pragma unroll 1
        for (int part = 0; part < 2; part++) {
          mbar_wait(bars + 8 * ((part ? B_SS3 : B_SS2) + sw), 0);
          if (lane == 0) {
            tma_store2(&p.hsS, fa, ra + 32 * part, stg + 2048 * part);
            tma_store2(&p.hsS, fa + 32, rb + 32 * part, stg + 5120 + 2048 * part);
          }
          __syncwarp();
        }
        mbar_wait(bars + 8 * (B_SG + sw), 0);
        if (lane == 0) {
          tma_store2(&p.hsS2, fa, ra + 64, stg + 4096);
          tma_store2(&p.hsS2, fa + 32, rb + 64, stg + 5120 + 4096);
          store_commit_wait();
          mbar_arrive(bars + 8 * (B_SD + sw));
          flag_release(&g_flag[(F_1 + ti) * 32]);
        }
        __syncwarp();
        mbar_wait(bars + 8 * (B_SG + sw), 1);
        if (lane == 0) {
          tma_store2(&p.x1S, 128 * fj + 64 * sw, TT * ti, stg);
          if (!sw) {
            store_commit_wait();
            mbar_arrive(bars + 8 * B_SD);
            flag_release(&g_flag[(F_2 + 2 * ti) * 32]);
          }
        }
        __syncwarp();
        mbar_wait(bars + 8 * (B_SS + sw), 0);
        if (lane == 0) {
          bulk_store(g_st + (2 * fj + sw) * 2176 + TT * ti, sb + XST + sw * 640, 640);
          store_commit_wait();
          if (sw) mbar_arrive(bars + 8 * (B_SD + 1));
          flag_release(&g_flag[(F_S + ti) * 32]);
          if (sw) { flag_add(&g_flag[(F_2 + 2 * ti + 1) * 32]); }
        }
        __syncwarp();
        if (b < 126) {
          if (sw) {
            unsigned ep;
            asm volatile("ld.relaxed.gpu.global.u32 %0, [%1];" : "=r"(ep) : "l"(&g_epoch) : "memory");
            poll3(&g_flag[(F_S + (TT3 * t3) / TT) * 32], &g_flag[(F_S + (TT3 * t3) / TT + 1) * 32], &g_flag[(F_S + min((TT3 * t3 + TT3 - 1) / TT, 25)) * 32], (ep + 1) * 10u);
            if (elect()) {
              mbar_expect(bars + 8 * B_STRAW, 10 * 1232);
              tma_load2(sb + STRAW, &p.stL, (TT3 * t3) & ~1, 0, bars + 8 * B_STRAW);
            }
            mbar_wait(bars + 8 * B_STRAW, 0);
#pragma unroll 1
            for (int r = lane; r < 152; r += 32) {
              float s = 0.f, ss = 0.f;
#pragma unroll
              for (int i = 0; i < 10; i++) { const float2 v = lds64f(sb + STRAW + i * 1232 + (r + (t3 & 1)) * 8); s += v.x; ss += v.y; }
              const float m = s * (1.f / D_);
              const float rs = 0.5f * rsqrtf(fmaxf(ss * (1.f / D_) - m * m, 0.f) + EPS);
              sts64f(sb + ST3 + r * 8, rs, -m * rs);
            }
            __syncwarp();
            if (lane == 0) { mbar_arrive(bars + 8 * B_ST3); }
            __syncwarp();
          }
#pragma unroll 1
          for (int w = sw; w < 3; w += 2) {
            mbar_wait(bars + 8 * (B_SS2 + w), w < 2);
            if (lane == 0) tma_store2(&p.HL, 192 * f3 + 64 * w, TT3 * t3, stg);
            __syncwarp();
            mbar_wait(bars + 8 * (B_SG + w), 0);
            if (lane == 0) {
              tma_store2(&p.HS, 192 * f3 + 64 * w, TT3 * t3 + TT, stg + 10240);
              store_commit_wait();
              mbar_arrive(bars + 8 * (B_SD + w));
              flag_release(&g_flag[(F_3 + w) * 32]);
            }
            __syncwarp();
          }
        }
        mbar_wait(bars + 8 * (B_SG + sw), b < 126);
        if (elect()) {
          tma_store2(&p.outS, 128 * fj + 64 * sw, TT * ti, stg);
          store_commit_wait();
        }
      }
    }
    __syncwarp();
  } else {
    asm volatile("setmaxnreg.inc.sync.aligned.u32 160;");
    const int w = warp & 3, g = lane >> 2, lt = tid & 127;
    const bool lead = lt == 0;
    if (b >= 128) {
      mbar_wait(bars + 8 * B_X, 0);
      if (tid < 320) {
        float a0 = 0.f, a1 = 0.f;
#pragma unroll 16
        for (int r = 0; r < 160; r++) { const uint32_t v = lds32(sb + r * 1280 + tid * 4); a0 += bf_lo(v); a1 += bf_hi(v); }
        reinterpret_cast<float2*>(g_cs1)[(b - 128) * 320 + tid] = make_float2(a0, a1);
        __threadfence();
      }
      bar_sync(7, 384);
      if (tid == 0) { flag_add(&g_flag[F_C * 32]); mbar_arrive(bars + 8 * B_CS); }
    } else {
      mbar_wait(bars + 8 * B_X, 0);
      if (warp < 8) {
        const int row = 2 * warp + (lane >> 4);
        float xv[40];
#pragma unroll
        for (int i = 0; i < 5; i++) {
          uint4 v = lds128(sb + PX + ((2 * i + ((lane >> 3) & 1)) * 16 + row) * 128 + (lane & 7) * 16);
          xv[8 * i] = bf_lo(v.x); xv[8 * i + 1] = bf_hi(v.x); xv[8 * i + 2] = bf_lo(v.y); xv[8 * i + 3] = bf_hi(v.y);
          xv[8 * i + 4] = bf_lo(v.z); xv[8 * i + 5] = bf_hi(v.z); xv[8 * i + 6] = bf_lo(v.w); xv[8 * i + 7] = bf_hi(v.w);
        }
        float s0 = 0.f, s1 = 0.f, s2 = 0.f, s3 = 0.f;
#pragma unroll
        for (int i = 0; i < 40; i += 4) { s0 += xv[i]; s1 += xv[i + 1]; s2 += xv[i + 2]; s3 += xv[i + 3]; }
        float s = (s0 + s1) + (s2 + s3);
#pragma unroll
        for (int o = 8; o; o >>= 1) s += __shfl_xor_sync(0xffffffffu, s, o);
        const float m = s * (1.f / D_);
        s0 = s1 = s2 = s3 = 0.f;
#pragma unroll
        for (int i = 0; i < 40; i += 4) {
          const float a0 = xv[i] - m, a1 = xv[i + 1] - m, a2 = xv[i + 2] - m, a3 = xv[i + 3] - m;
          s0 = fmaf(a0, a0, s0); s1 = fmaf(a1, a1, s1); s2 = fmaf(a2, a2, s2); s3 = fmaf(a3, a3, s3);
        }
        s = (s0 + s1) + (s2 + s3);
#pragma unroll
        for (int o = 8; o; o >>= 1) s += __shfl_xor_sync(0xffffffffu, s, o);
        if ((lane & 15) == 0) sts64f(sb + ROWST + row * 8, m, rsqrtf(s * (1.f / D_) + EPS));
      }
      bar_sync(7, 384);
      {
        const float2 st0 = lds64f(sb + ROWST + g * 8), st1 = lds64f(sb + ROWST + (8 + g) * 8);
#pragma unroll 1
        for (int u = warp; u < 40; u += 12) {
          mbar_wait(bars + 8 * (B_KV + (u >> 3)), 0);
          pre_unit(sb, u >> 3, u & 7, lane, st0, st1);
          warp_signal(bars + 8 * (B_PST + (u >> 3)), lane);
        }
#pragma unroll 1
        for (int r = wg; r < (wg < 2 ? wg + 1 : 5); r++) {
          mbar_wait(bars + 8 * (B_F + r), 0);
          build_table(sb, r, lt);
          bar_sync(1 + wg, 128);
          if (lead) mbar_arrive(bars + 8 * (B_TAB + r));
        }
      }
      {
        uint32_t tid2;
        asm volatile("mov.u32 %0, %%tid.x;" : "=r"(tid2));
        const int lane = tid2 & 31, g = lane >> 2, t = lane & 3;
        const uint32_t ex = sb + EXCH + wg * 12288 + lane * 8;
        const int L0 = 128 * w + 8 + g;
        const uint32_t ta0 = sb + ((g & 1) ? TAB_O + ((2047 - L0) / 2 + t) * 4 : TAB_E + ((2048 - L0) / 2 + t) * 4);
        uint32_t A[16][4];
        conv_load_a<0>(A, ta0 + TABB(wg));
        conv_load_a<8>(A, ta0 + TABB(wg));
        const uint32_t qc0 = sb + w * 512 + t * 64 + (t >= 2 ? 32 : 0) + (g & 1) * 16 + (g >> 1) * 4;
        const uint32_t hst0 = sb + w * 256 + t * 32 + (((g & 1) ^ ((b >> 2) & 1)) << 4) + (g >> 1) * 4;
#pragma unroll 1
        for (int r = wg; r < 5; r += 3) {
          const uint64_t db = mkdesc(sb + UB(r) + 128 - 16, 16, 0x8);
          const int nx = r == 1 ? 2 : (r == 0 || r == 3) ? 1 : 0;
          float d0[32], d1[32], c0 = 0.f, c1 = 0.f;
          const uint32_t qc = qc0 + QCB(r), hst = hst0 + TABB(r);
          if (r >= 3) { mbar_wait(bars + 8 * (B_TAB + r), 0); conv_load_a<0>(A, ta0 + TABB(r)); }
          mbar_wait(bars + 8 * (B_U + r), 0);
          if (r > 0) bar_sync(4 + wg, 256);
          WG_FENCE();
          conv_mma<0, 0, 0>(d0, A, db);
          WG_COMMIT();
          conv_mma<1, 0, 1>(d1, A, db);
          WG_COMMIT();
          bar_arrive(4 + nx, 256);
          if (r >= 3) conv_load_a<8>(A, ta0 + TABB(r));
          mbar_wait(bars + 8 * (B_QC + r), 0);
          WG_WAIT(1);
          conv_drain<0>(d0, c0, c1, ex, qc, hst, wg, w, lane);
          WG_WAIT(0);
          conv_drain<1>(d1, c0, c1, ex, qc, hst, wg, w, lane);
          bar_sync(4 + wg, 256);
          WG_FENCE();
          conv_mma<2, 0, 2>(d0, A, db);
          WG_COMMIT();
          conv_mma<3, 0, 3>(d1, A, db);
          WG_COMMIT();
          if (r < 4) bar_arrive(4 + nx, 256);
          WG_WAIT(1);
          conv_drain<2>(d0, c0, c1, ex, qc, hst, wg, w, lane);
          WG_WAIT(0);
          conv_drain<3>(d1, c0, c1, ex, qc, hst, wg, w, lane);
          warp_signal(bars + 8 * (B_HST + r), lane);
        }
      }
    }
    if (b < 130) {
      uint32_t res[20];
      uint32_t tid2;
      asm volatile("mov.u32 %0, %%tid.x;" : "=r"(tid2));
      const int lane = tid2 & 31, g = lane >> 2, t = lane & 3, lt = tid2 & 127;
      const bool lead = lt == 0;
      const int m_ = lane >> 3, rho = lane & 7;
      const uint32_t stg = sb + GST + (wg & 1) * 19456;
      float d[40];
#pragma unroll
      for (int i = 0; i < 40; i++) d[i] = 0.f;
      if (wg < 2) {
        gemm_seg<0, 4, 4, 16384, B_WF2, B_WE2, 1, 10, 10240, B_XE>(d, sb, 10, wg * 8192, 0, 0, 0, true, lt, -1);
        mbar_wait(bars + 8 * B_TOK, 0);
        const uint32_t stg1 = stg + (w >> 1) * 5120;
        const float cs0 = __uint_as_float(lds32(sb + CS1S + (64 * wg + 16 * w + g) * 4)), cs1 = __uint_as_float(lds32(sb + CS1S + (64 * wg + 16 * w + g + 8) * 4));
#pragma unroll
        for (int j = 0; j < 10; j += 2) {
          uint32_t pk[4];
#pragma unroll
          for (int jj = 0; jj < 2; jj++) {
            const int o = 4 * (j + jj);
            const float4 sa = lds128f(sb + TOKST + (8 * (j + jj) + 2 * t) * 16), sc = lds128f(sb + TOKST + (8 * (j + jj) + 2 * t + 1) * 16);
            pk[2 * jj] = gelu_pair(fmaf(d[o], sa.z, sa.w * cs0), fmaf(d[o + 1], sc.z, sc.w * cs0));
            pk[2 * jj + 1] = gelu_pair(fmaf(d[o + 2], sa.z, sa.w * cs1), fmaf(d[o + 3], sc.z, sc.w * cs1));
          }
          const int tok = 8 * (j + (m_ >> 1)) + rho, chunk = 2 * (w & 1) + (m_ & 1);
          stsm4t(stg1 + tok * 64 + ((chunk ^ ((tok >> 1) & 3)) << 4), pk[0], pk[1], pk[2], pk[3]);
          if (j == 2 || j >= 6) warp_signal(bars + 8 * ((j == 8 ? B_SG : j == 6 ? B_SS3 : B_SS2) + wg), lane);
        }
      }
      if (wg == 2) {
        float s[8], ss[8];
#pragma unroll
        for (int i = 0; i < 8; i++) { s[i] = 0.f; ss[i] = 0.f; }
        mbar_wait(bars + 8 * B_XF, 0);
        {
          const float* cp = g_cs1 + 128 * fj + lt;
          sts32(sb + CS1S + lt * 4, __float_as_uint((__ldcg(cp) + __ldcg(cp + D_)) + (__ldcg(cp + 2 * D_) + __ldcg(cp + 3 * D_))));
        }
        if (b < 128) mbar_wait(bars + 8 * (B_HST + 4), 0);
        if (w < 3) {
          const bool act = lt < 80;
#pragma unroll 1
          for (int c = 0; c < 5; c++) {
            mbar_wait(bars + 8 * (B_XF + c), 0);
            uint4 v[16];
#pragma unroll
            for (int k1 = 0; k1 < 16; k1++) v[k1] = lds128(sb + XR + c * 20480 + k1 * 1280 + min(lt, 79) * 16);
            if (c == 4) {
              asm volatile("" ::"r"(v[15].x) : "memory");
              bar_arrive(7, 352);
            }
#pragma unroll
            for (int k1 = 0; k1 < 16; k1++) {
              float f;
              f = bf_lo(v[k1].x); s[0] += f; ss[0] = fmaf(f, f, ss[0]); f = bf_hi(v[k1].x); s[1] += f; ss[1] = fmaf(f, f, ss[1]);
              f = bf_lo(v[k1].y); s[2] += f; ss[2] = fmaf(f, f, ss[2]); f = bf_hi(v[k1].y); s[3] += f; ss[3] = fmaf(f, f, ss[3]);
              f = bf_lo(v[k1].z); s[4] += f; ss[4] = fmaf(f, f, ss[4]); f = bf_hi(v[k1].z); s[5] += f; ss[5] = fmaf(f, f, ss[5]);
              f = bf_lo(v[k1].w); s[6] += f; ss[6] = fmaf(f, f, ss[6]); f = bf_hi(v[k1].w); s[7] += f; ss[7] = fmaf(f, f, ss[7]);
            }
          }
          const int k0 = (lt >> 1) & 7, half = (lt & 1) ^ (k0 >> 2);
#pragma unroll
          for (int i = 0; i < 4; i++) {
            const bool up = k0 & 4;
            const float a = up ? s[i] : s[i + 4], c = up ? ss[i] : ss[i + 4];
            s[i] = (up ? s[i + 4] : s[i]) + __shfl_xor_sync(0xffffffffu, a, 9);
            ss[i] = (up ? ss[i + 4] : ss[i]) + __shfl_xor_sync(0xffffffffu, c, 9);
          }
#pragma unroll
          for (int i = 0; i < 2; i++) {
            const bool up = k0 & 2;
            const float a = up ? s[i] : s[i + 2], c = up ? ss[i] : ss[i + 2];
            s[i] = (up ? s[i + 2] : s[i]) + __shfl_xor_sync(0xffffffffu, a, 4);
            ss[i] = (up ? ss[i + 2] : ss[i]) + __shfl_xor_sync(0xffffffffu, c, 4);
          }
          {
            const bool up = k0 & 1;
            const float a = up ? s[0] : s[1], c = up ? ss[0] : ss[1];
            s[0] = (up ? s[1] : s[0]) + __shfl_xor_sync(0xffffffffu, a, 2);
            ss[0] = (up ? ss[1] : ss[0]) + __shfl_xor_sync(0xffffffffu, c, 2);
          }
          if (act) {
            const float m = s[0] * (1.f / D_);
            const float var = fmaxf(ss[0] * (1.f / D_) - m * m, 0.f);
            const float r2 = rsqrtf(var + EPS);
            const int tok = (lt >> 4) * 16 + half * 8 + k0;
            const float r23 = TT * ti + tok < S_ ? 0.5f * r2 * rsqrtf(var * r2 * r2 + EPS) : 0.f;
            sts128(sb + TOKST + tok * 16, __float_as_uint(r2), __float_as_uint(-m * r2), __float_as_uint(r23), __float_as_uint(-m * r23));
          }
        }
        __syncwarp();
        if (lane == 0) { mbar_arrive(bars + 8 * B_TOK); mbar_arrive(bars + 8 * B_XFREE); }
      } else {
        {
          const uint32_t hb = sb + XR + (2 * fj + wg) * 10240 + 2 * w * 1280 + g * 32 + t * 4;
#pragma unroll
          for (int j = 0; j < 10; j++) {
            const uint32_t a = hb + (j >> 1) * 256 + (((j & 1) ^ (g >> 2)) << 4);
            res[2 * j] = lds32(a); res[2 * j + 1] = lds32(a + 1280);
          }
        }
#pragma unroll
        for (int j = 0; j < 10; j++) {
          const int o = 4 * j, q = 2 * j;
          const float2 sa = lds64f(sb + TOKST + (8 * j + 2 * t) * 16), sc = lds64f(sb + TOKST + (8 * j + 2 * t + 1) * 16);
          d[o] = fmaf(bf_lo(res[q]), sa.x, sa.y); d[o + 1] = fmaf(bf_hi(res[q]), sc.x, sc.y);
          d[o + 2] = fmaf(bf_lo(res[q + 1]), sa.x, sa.y); d[o + 3] = fmaf(bf_hi(res[q + 1]), sc.x, sc.y);
        }
        bar_sync(1 + wg, 128);
        if (lead) { mbar_arrive(bars + 8 * B_XFREE); }
        if (wg == 1) { mbar_wait(bars + 8 * B_SD, 0); mbar_wait(bars + 8 * B_SD, 1); }
        gemm_seg<1, 8, 4, 16384, B_WF2, B_WE2, 2, 5, 20480, B_XE>(d, sb, 5, 0, 2 + wg, wg ? 0x8 : 0x3, 0x1F, wg == 0, lt, -1);
        mbar_wait(bars + 8 * (B_SD + wg), 0);
#pragma unroll
        for (int j = 0; j < 10; j += 2) {
          uint32_t pk[4];
#pragma unroll
          for (int i = 0; i < 4; i++) {
            pk[i] = pack_bf16(d[4 * j + 2 * i], d[4 * j + 2 * i + 1]);
            res[2 * j + i] = pack_bf16(bf_lo(res[2 * j + i]) + bf_lo(pk[i]), bf_hi(res[2 * j + i]) + bf_hi(pk[i]));
          }
          const int tok = 8 * (j + (m_ >> 1)) + rho, chunk = 2 * w + (m_ & 1);
          stsm4t(stg + tok * 128 + ((chunk ^ (tok & 7)) << 4), pk[0], pk[1], pk[2], pk[3]);
        }
        warp_signal(bars + 8 * (B_SG + wg), lane);
        bar_sync(1 + wg, 128);
        if (lt < 80) {
          float s = 0.f, ss = 0.f;
          uint4 v[8];
#pragma unroll
          for (int i = 0; i < 8; i++) v[i] = lds128(stg + lt * 128 + (((i + lt) & 7) << 4));
          float s1 = 0.f, ss1 = 0.f;
#pragma unroll
          for (int i = 0; i < 8; i++) {
            float f;
            f = bf_lo(v[i].x); s += f; ss = fmaf(f, f, ss); f = bf_hi(v[i].x); s1 += f; ss1 = fmaf(f, f, ss1);
            f = bf_lo(v[i].y); s += f; ss = fmaf(f, f, ss); f = bf_hi(v[i].y); s1 += f; ss1 = fmaf(f, f, ss1);
            f = bf_lo(v[i].z); s += f; ss = fmaf(f, f, ss); f = bf_hi(v[i].z); s1 += f; ss1 = fmaf(f, f, ss1);
            f = bf_lo(v[i].w); s += f; ss = fmaf(f, f, ss); f = bf_hi(v[i].w); s1 += f; ss1 = fmaf(f, f, ss1);
          }
          s += s1; ss += ss1;
          sts64f(sb + XST + wg * 640 + lt * 8, s, ss);
        }
        warp_signal(bars + 8 * (B_SS + wg), lane);
      }
      mbar_wait(bars + 8 * (B_XE + 4), 0);
      if (warp == 8) {
        if (lane < 8) {
#pragma unroll
          for (int s = 0; s < 5; s++) sts128(sb + XR + s * 19456 + TT3 * 128 + lane * 16, 0x3F803F80u, 0x3F803F80u, 0x3F803F80u, 0x3F803F80u);
        }
        warp_signal(bars + 8 * B_ONES, lane);
      }
      if (b < 126) {
        float d[76];
#pragma unroll
        for (int i = 0; i < 76; i++) d[i] = 0.f;
        mbar_wait(bars + 8 * B_ONES, 0);
        gemm_seg<2, 4, 3, 24576, B_WF3, B_WE3, 1, 5, 19456, B_X3E>(d, sb, 5, wg * 8192, 0, 0, 0, true, lt, -1);
        if (wg == 0) bar_sync(7, 384); else bar_arrive(7, 384);
        if (wg > 0) bar_sync(4 + wg, 256);
        if (wg == 0) {
          gemm_seg<2, 4, 9, 8192, B_WF1, B_WE1, 1, 5, 19456, B_X3E>(d, sb, 5, 0, 6, 0, 0x1F, true, lt, 5);
        } else {
          const uint32_t s0 = wg == 1 ? 2 : 7, s2 = wg == 1 ? 4 : 0;
          const uint64_t la0 = mkdesc(sb + WR + s0 * 8192, 1024, 0x40000040), la2 = mkdesc(sb + WR + s2 * 8192, 1024, 0x40000040), lb = mkdesc(sb + XR, 16, 0x40000040);
          const uint32_t w0 = bars + 8 * (B_WF1 + s0), w2 = bars + 8 * (B_WF1 + s2);
          mbar_wait2(w0, wg - 1, w0 + 8, wg - 1);
          mbar_wait2(w2, wg - 1, w2 + 8, wg - 1);
          reg_fence(d);
          WG_FENCE();
#pragma unroll
          for (int c = 0; c < 5; c++) {
            if (c == 4) { mbar_wait(w2 + 16, 1); WG_FENCE(); }
#pragma unroll
            for (int k = 0; k < 4; k++) wg_ss152k(d, (c < 2 ? la0 + c * 512 : la2 + (c - 2) * 512) + k * 128, lb + c * 1216 + k * 2);
          }
          WG_COMMIT();
          if (wg == 1) bar_arrive(6, 256);
          WG_WAIT(0);
          reg_fence(d);
          if (lt < 10) mbar_arrive(lt < 5 ? bars + 8 * (B_X3E + lt) : (lt < 7 ? w0 + 8 * (lt - 5) : w2 + 8 * (lt - 7)) + 8 * (B_WE1 - B_WF1));
        }
        mbar_wait(bars + 8 * B_ST3, 0);
        const float cs0 = __shfl_sync(0xffffffffu, d[73], lane | 3), cs1 = __shfl_sync(0xffffffffu, d[75], lane | 3);
#pragma unroll
        for (int part = 0; part < 2; part++) {
          const int j0 = part ? 10 : 0, j1 = part ? 19 : 10;
          uint32_t pk[20];
#pragma unroll
          for (int j = j0; j < j1; j++) {
            const float4 sa = lds128f(sb + ST3 + (8 * j + 2 * t) * 8);
            const int o = 4 * j, q = 2 * (j - j0);
            pk[q] = gelu_pair(fmaf(d[o], sa.x, sa.y * cs0), fmaf(d[o + 1], sa.z, sa.w * cs0));
            pk[q + 1] = gelu_pair(fmaf(d[o + 2], sa.x, sa.y * cs1), fmaf(d[o + 3], sa.z, sa.w * cs1));
          }
          if (!part) mbar_wait(bars + 8 * (B_SD + (wg & 1)), wg == 2 ? 0 : 1);
#pragma unroll
          for (int j = j0; j < j1; j += 2) {
            const int tok = 8 * (j + (m_ >> 1)) + rho, chunk = 2 * w + (m_ & 1), q = 2 * (j - j0);
            const uint32_t a = stg + tok * 128 + ((chunk ^ (tok & 7)) << 4);
            if (j + 1 < 19) stsm4t(a, pk[q], pk[q + 1], pk[q + 2], pk[q + 3]); else stsm2t(a, pk[q], pk[q + 1]);
          }
          if (!part) warp_signal(bars + 8 * (B_SS2 + wg), lane);
        }
        warp_signal(bars + 8 * (B_SG + wg), lane);
      }
      if (wg < 2) {
        float d[40];
#pragma unroll
        for (int j = 0; j < 20; j++) { d[2 * j] = bf_lo(res[j]); d[2 * j + 1] = bf_hi(res[j]); }
        gemm_seg<3, 4, 6, 16384, B_WF4, B_WE4, 1, 6, 10240, B_XE>(d, sb, 27, wg * 8192 - 32768, 4, 0, 0, false, lt, -1);
        if (b < 126) mbar_wait(bars + 8 * (B_SD + (wg ? 1 : 2)), 0); else mbar_wait(bars + 8 * (B_SD + wg), 1);
#pragma unroll
        for (int j = 0; j < 10; j += 2) {
          const int tok = 8 * (j + (m_ >> 1)) + rho, chunk = 2 * w + (m_ & 1);
          stsm4t(stg + tok * 128 + ((chunk ^ (tok & 7)) << 4), pack_bf16(d[4 * j], d[4 * j + 1]), pack_bf16(d[4 * j + 2], d[4 * j + 3]),
                 pack_bf16(d[4 * j + 4], d[4 * j + 5]), pack_bf16(d[4 * j + 6], d[4 * j + 7]));
        }
        warp_signal(bars + 8 * (B_SG + wg), lane);
      }
    }
  }
}

typedef CUresult (*EncFn)(CUtensorMap*, CUtensorMapDataType, cuuint32_t, void*, const cuuint64_t*, const cuuint64_t*, const cuuint32_t*,
                          const cuuint32_t*, CUtensorMapInterleave, CUtensorMapSwizzle, CUtensorMapL2promotion, CUtensorMapFloatOOBfill);

void make2d(EncFn enc, CUtensorMap* tm, const void* ptr, uint64_t inner, uint64_t outer, uint32_t bi, uint32_t bo, CUtensorMapSwizzle sw) {
  cuuint64_t gd[2] = {inner, outer};
  cuuint64_t gs[1] = {inner * 2};
  cuuint32_t bd[2] = {bi, bo}, es[2] = {1, 1};
  CUresult rr = enc(tm, CU_TENSOR_MAP_DATA_TYPE_BFLOAT16, 2, const_cast<void*>(ptr), gd, gs, bd, es, CU_TENSOR_MAP_INTERLEAVE_NONE, sw,
      CU_TENSOR_MAP_L2_PROMOTION_L2_128B, CU_TENSOR_MAP_FLOAT_OOB_FILL_NONE);
  (void)rr;
}

void make3w(EncFn enc, CUtensorMap* tm, const void* ptr, uint64_t cols, uint64_t rows, uint32_t nb, uint32_t br = 64) {
  cuuint64_t gd[3] = {64, rows, cols / 64};
  cuuint64_t gs[2] = {cols * 2, 128};
  cuuint32_t bd[3] = {64, br, nb}, es[3] = {1, 1, 1};
  enc(tm, CU_TENSOR_MAP_DATA_TYPE_BFLOAT16, 3, const_cast<void*>(ptr), gd, gs, bd, es, CU_TENSOR_MAP_INTERLEAVE_NONE, CU_TENSOR_MAP_SWIZZLE_128B,
      CU_TENSOR_MAP_L2_PROMOTION_L2_128B, CU_TENSOR_MAP_FLOAT_OOB_FILL_NONE);
}

}

extern "C" void kernel_launch(void* const* d_in, const int* in_sizes, int n_in, void* d_out, int out_size) {
  (void)in_sizes; (void)n_in; (void)out_size;
  static EncFn enc = nullptr;
  static void *kvT, *qc, *hT, *hs, *x1, *H, *st;
  if (!enc) {
    void* fn = nullptr;
    cudaDriverEntryPointQueryResult qr;
    cudaGetDriverEntryPoint("cuTensorMapEncodeTiled", &fn, cudaEnableDefault, &qr);
    enc = (EncFn)fn;
    cudaFuncSetAttribute(fused_kernel, cudaFuncAttributeMaxDynamicSharedMemorySize, SMEM_BYTES);
    cudaGetSymbolAddress(&kvT, g_kvT); cudaGetSymbolAddress(&qc, g_qc); cudaGetSymbolAddress(&hT, g_hT);
    cudaGetSymbolAddress(&hs, g_hs); cudaGetSymbolAddress(&x1, g_x1); cudaGetSymbolAddress(&H, g_H); cudaGetSymbolAddress(&st, g_st);
  }
  Params p;
  p.shift_k = (const __nv_bfloat16*)d_in[3]; p.ssm_k = (const __nv_bfloat16*)d_in[4]; p.ssm_D = (const __nv_bfloat16*)d_in[5];
  p.pw1 = (const __nv_bfloat16*)d_in[7]; p.pw2 = (const __nv_bfloat16*)d_in[8]; p.pw3 = (const __nv_bfloat16*)d_in[9]; p.pw4 = (const __nv_bfloat16*)d_in[10];
  for (int i = 0; i < 3; i++) {
    cuuint64_t gd[3] = {64, S_, 10};
    cuuint64_t gs[2] = {D_ * 2, 128};
    cuuint32_t bd[3] = {64, i == 1 ? 19u : 16u, i == 0 ? 10u : 2u}, es[3] = {1, 1, 1};
    enc(i == 0 ? &p.xin : i == 1 ? &p.kin : &p.vin, CU_TENSOR_MAP_DATA_TYPE_BFLOAT16, 3, d_in[i], gd, gs, bd, es, CU_TENSOR_MAP_INTERLEAVE_NONE,
        CU_TENSOR_MAP_SWIZZLE_128B, CU_TENSOR_MAP_L2_PROMOTION_L2_128B, CU_TENSOR_MAP_FLOAT_OOB_FILL_NONE);
  }
  make3w(enc, &p.w1p, p.pw1, D_, D_, 2);
  make3w(enc, &p.w3t, p.pw3, F_, D_, 3);
  make3w(enc, &p.w4p, p.pw4, D_, F_, 2);
  make2d(enc, &p.w2d, p.pw2, D_, D_, 64, 128, CU_TENSOR_MAP_SWIZZLE_128B);
  make2d(enc, &p.w3, p.pw3, F_, D_, 64, 64, CU_TENSOR_MAP_SWIZZLE_128B);
  make2d(enc, &p.kvT, kvT, S_, D_, 16, 128, CU_TENSOR_MAP_SWIZZLE_32B);
  make2d(enc, &p.qc, qc, 2 * S_, D_, 32, 128, CU_TENSOR_MAP_SWIZZLE_64B);
  {
    cuuint64_t gd[5] = {16, 8, 5, 80, 26};
    cuuint64_t gs[4] = {32, 256, 1280, 102400};
    cuuint32_t bd[5] = {16, 1, 5, 1, 26}, es[5] = {1, 1, 1, 1, 1};
    CUresult rr = enc(&p.hT, CU_TENSOR_MAP_DATA_TYPE_BFLOAT16, 5, hT, gd, gs, bd, es, CU_TENSOR_MAP_INTERLEAVE_NONE, CU_TENSOR_MAP_SWIZZLE_NONE,
        CU_TENSOR_MAP_L2_PROMOTION_NONE, CU_TENSOR_MAP_FLOAT_OOB_FILL_NONE);
    (void)rr;
  }
  {
    cuuint64_t gd[2] = {2176, 10};
    cuuint64_t gs[1] = {2176 * 8};
    cuuint32_t bd[2] = {154, 10}, es[2] = {1, 1};
    enc(&p.stL, CU_TENSOR_MAP_DATA_TYPE_UINT64, 2, st, gd, gs, bd, es, CU_TENSOR_MAP_INTERLEAVE_NONE, CU_TENSOR_MAP_SWIZZLE_NONE,
        CU_TENSOR_MAP_L2_PROMOTION_NONE, CU_TENSOR_MAP_FLOAT_OOB_FILL_NONE);
  }
  make2d(enc, &p.hsS, hs, D_, S_ + 2, 32, 32, CU_TENSOR_MAP_SWIZZLE_64B);
  make2d(enc, &p.hsS2, hs, D_, S_ + 2, 32, 16, CU_TENSOR_MAP_SWIZZLE_64B);
  make3w(enc, &p.hsL, (__nv_bfloat16*)hs + 2 * D_, D_, S_, 2, TT);
  make2d(enc, &p.x1S, x1, D_, S_, 64, TT, CU_TENSOR_MAP_SWIZZLE_128B);
  make2d(enc, &p.x1L, x1, D_, S_, 64, TT3, CU_TENSOR_MAP_SWIZZLE_128B);
  make2d(enc, &p.HS, H, F_, S_, 64, TT3 - TT, CU_TENSOR_MAP_SWIZZLE_128B);
  make2d(enc, &p.HL, H, F_, S_, 64, TT, CU_TENSOR_MAP_SWIZZLE_128B);
  make2d(enc, &p.outS, d_out, D_, S_, 64, TT, CU_TENSOR_MAP_SWIZZLE_128B);
  fused_kernel<<<NCTA, NTHR, SMEM_BYTES, cudaStreamPerThread>>>(p);
}
```

```cpp
#include <cuda_runtime.h>
#include <cuda_bf16.h>
#include <cuda.h>
#include <stdint.h>

namespace {

constexpr int S_ = 2048, D_ = 640, F_ = 1728;
constexpr int NCTA = 132;
constexpr int NTHR = 512;
constexpr int TT = 80;
constexpr int TT3 = 151;
constexpr float EPS = 1e-5f;

constexpr uint32_t XR = 0;
constexpr uint32_t WR = 102400;
constexpr uint32_t CR = 176128;
constexpr uint32_t TAB_E = 3 * 4, TAB_O = 1044 * 4;
__host__ __device__ constexpr uint32_t QCB(int r) { return r < 4 ? 20992 * r : CR + 36864; }
__host__ __device__ constexpr uint32_t TABB(int r) { return 20992 * r + (r < 4 ? 8192 : 0); }
__host__ __device__ constexpr uint32_t UB(int r) { return TABB(r) + 8320; }
constexpr uint32_t PK = WR;
constexpr uint32_t PX = WR + 5 * 9216;
constexpr uint32_t PSK = PX + 20480;
__host__ __device__ constexpr uint32_t RAWB(int r) { return r < 2 ? CR + 8192 * r : WR + 4096 * r; }
constexpr uint32_t EXCH = CR;
constexpr uint32_t GST = CR;
constexpr uint32_t STRAW = CR + 29696;
constexpr uint32_t MISC = CR + 45056;
constexpr uint32_t BARS = MISC;
constexpr uint32_t ROWST = MISC + 4096;
constexpr uint32_t TOKST = MISC + 1024;
constexpr uint32_t CS1S = MISC + 2304;
constexpr uint32_t ST3 = MISC + 2816;
constexpr uint32_t XST = MISC + 4864;
constexpr uint32_t SMEM_BYTES = 232448;
enum { B_X = 0, B_KV = 1  , B_F = 6  , B_U = 11  , B_QC = 16  , B_TAB = 21  , B_PST = 26  ,
       B_HST = 31  , B_HDONE = 36  , B_ONES = 41, B_CS, B_TOK, B_ST3, B_XFREE,
       B_SG = 47  , B_SD = 50  , B_SS = 53  ,
       B_WF1 = 55  , B_WE1 = 64  , B_WF2 = 73  , B_WE2 = 77  , B_WF3 = 81  , B_WE3 = 84  ,
       B_XF = 87  , B_SS3 = 92  , B_XE = 97  , B_X3E = 107  , B_WF4 = 112  , B_WE4 = 118  , B_STRAW = 124, B_SS2 = 125  , B_NUM = 128 };
enum { F_P = 0, F_C = 5  , F_1 = 10  , F_2 = 36  , F_S = 88  , F_3 = 114  , F_NUM = 117 };

struct Params {
  CUtensorMap w1p, w2d, w3t, w3, w4p, kvT, qc, hT, hsS, hsS2, hsL, x1S, x1L, HS, HL, outS, kin, vin, xin, stL;
  const __nv_bfloat16 *shift_k, *ssm_k, *ssm_D, *pw1, *pw2, *pw3, *pw4;
};

}

__device__ __align__(1024) __nv_bfloat16 g_kvT[D_ * S_];
__device__ __align__(1024) __nv_bfloat16 g_qc[D_ * S_ * 2];
__device__ __align__(1024) __nv_bfloat16 g_hT[26 * D_ * TT];
__device__ __align__(1024) __nv_bfloat16 g_hs[(S_ + 2) * D_];
__device__ __align__(1024) __nv_bfloat16 g_x1[S_ * D_];
__device__ __align__(1024) __nv_bfloat16 g_H[S_ * F_];
__device__ __align__(1024) float2 g_st[10 * 2176];
__device__ __align__(1024) float g_cs1[4 * D_];
__device__ __align__(1024) unsigned g_flag[F_NUM * 32];
__device__ unsigned g_epoch;

namespace {

__device__ __forceinline__ void mbar_init(uint32_t b, uint32_t c) { asm volatile("mbarrier.init.shared::cta.b64 [%0], %1;" ::"r"(b), "r"(c)); }
__device__ __forceinline__ void mbar_expect(uint32_t b, uint32_t bytes) {
  asm volatile("mbarrier.arrive.expect_tx.shared::cta.b64 _, [%0], %1;" ::"r"(b), "r"(bytes) : "memory");
}
__device__ __forceinline__ void mbar_arrive(uint32_t b) { asm volatile("mbarrier.arrive.shared::cta.b64 _, [%0];" ::"r"(b) : "memory"); }
__device__ __forceinline__ void mbar_wait(uint32_t b, uint32_t par) {
  asm volatile(
      "{.reg .pred p; .reg .u32 c; mov.u32 c, 0;\n"
      "WL: mbarrier.try_wait.parity.shared::cta.b64 p, [%0], %1;\n"
      "@p bra.uni WD;\n"
      "add.u32 c, c, 1; setp.lt.u32 p, c, 4000000; @p bra.uni WL; trap;\n"
      "WD: }" ::"r"(b), "r"(par) : "memory");
}
__device__ __forceinline__ void mbar_wait2(uint32_t b0, uint32_t p0, uint32_t b1, uint32_t p1) {
  asm volatile(
      "{.reg .pred p, q; .reg .u32 c; mov.u32 c, 0;\n"
      "WL: mbarrier.try_wait.parity.shared::cta.b64 p, [%0], %1;\n"
      "mbarrier.try_wait.parity.shared::cta.b64 q, [%2], %3;\n"
      "and.pred p, p, q;\n"
      "@p bra.uni WD;\n"
      "add.u32 c, c, 1; setp.lt.u32 p, c, 4000000; @p bra.uni WL; trap;\n"
      "WD: }" ::"r"(b0), "r"(p0), "r"(b1), "r"(p1) : "memory");
}
__device__ __forceinline__ void poll3(const unsigned* f0, const unsigned* f1, const unsigned* f2, unsigned target) {
  asm volatile(
      "{.reg .pred p; .reg .u32 a, b, c, n; mov.u32 n, 0;\n"
      "PL: ld.relaxed.gpu.global.u32 a, [%0]; ld.relaxed.gpu.global.u32 b, [%1]; ld.relaxed.gpu.global.u32 c, [%2];\n"
      "sub.u32 a, a, %3; sub.u32 b, b, %3; sub.u32 c, c, %3; or.b32 a, a, b; or.b32 a, a, c; setp.ge.s32 p, a, 0;\n"
      "@p bra.uni PD;\n"
      "add.u32 n, n, 1; setp.lt.u32 p, n, 4000000; @p bra.uni PL; trap;\n"
      "PD: }" ::"l"(f0), "l"(f1), "l"(f2), "r"(target) : "memory");
}
__device__ __forceinline__ void poll1(const unsigned* f, unsigned target) {
  asm volatile(
      "{.reg .pred p; .reg .u32 a, n; mov.u32 n, 0;\n"
      "PL: ld.relaxed.gpu.global.u32 a, [%0]; sub.u32 a, a, %1; setp.ge.s32 p, a, 0;\n"
      "@p bra.uni PD;\n"
      "add.u32 n, n, 1; setp.lt.u32 p, n, 4000000; @p bra.uni PL; trap;\n"
      "PD: }" ::"l"(f), "r"(target) : "memory");
}
__device__ __forceinline__ bool elect() {
  uint32_t p;
  asm volatile("{.reg .pred q; elect.sync _|q, 0xffffffff; selp.u32 %0,1,0,q;}" : "=r"(p));
  return p;
}
__device__ __forceinline__ void flag_add(unsigned* f) { asm volatile("red.relaxed.gpu.global.add.u32 [%0], 1;" ::"l"(f) : "memory"); }
__device__ __forceinline__ void tma_load3(uint32_t dst, const CUtensorMap* tm, int c0, int c1, int c2, uint32_t bar) {
  asm volatile("cp.async.bulk.tensor.3d.shared::cluster.global.mbarrier::complete_tx::bytes [%0], [%1, {%3,%4,%5}], [%2];" ::"r"(dst), "l"(tm), "r"(bar), "r"(c0), "r"(c1), "r"(c2) : "memory");
}
__device__ __forceinline__ void bulk_store(void* dst, uint32_t src, uint32_t bytes) {
  asm volatile("cp.async.bulk.global.shared::cta.bulk_group [%0], [%1], %2;" ::"l"(dst), "r"(src), "r"(bytes) : "memory");
}
__device__ __forceinline__ uint32_t swz128(uint32_t a) { return a ^ ((a >> 3) & 0x70u); }
__device__ __forceinline__ void bulk_load(uint32_t dst, const void* src, uint32_t bytes, uint32_t bar) {
  asm volatile("cp.async.bulk.shared::cluster.global.mbarrier::complete_tx::bytes [%0], [%1], %2, [%3];" ::"r"(dst), "l"(src), "r"(bytes), "r"(bar) : "memory");
}
__device__ __forceinline__ void tma_load2(uint32_t dst, const CUtensorMap* tm, int c0, int c1, uint32_t bar) {
  asm volatile("cp.async.bulk.tensor.2d.shared::cluster.global.mbarrier::complete_tx::bytes [%0], [%1, {%3,%4}], [%2];" ::"r"(dst), "l"(tm), "r"(bar), "r"(c0), "r"(c1) : "memory");
}
__device__ __forceinline__ void tma_store2(const CUtensorMap* tm, int c0, int c1, uint32_t src) {
  asm volatile("cp.async.bulk.tensor.2d.global.shared::cta.bulk_group [%0, {%2,%3}], [%1];" ::"l"(tm), "r"(src), "r"(c0), "r"(c1) : "memory");
}
__device__ __forceinline__ void tma_store5(const CUtensorMap* tm, int c0, int c1, int c2, int c3, int c4, uint32_t src) {
  asm volatile("cp.async.bulk.tensor.5d.global.shared::cta.bulk_group [%0, {%2,%3,%4,%5,%6}], [%1];" ::"l"(tm), "r"(src), "r"(c0), "r"(c1), "r"(c2), "r"(c3), "r"(c4) : "memory");
}
__device__ __forceinline__ void store_commit_wait() {
  asm volatile("cp.async.bulk.commit_group;" ::: "memory");
  asm volatile("cp.async.bulk.wait_group 0;" ::: "memory");
}
__device__ __forceinline__ void flag_release(unsigned* f) {
  asm volatile("fence.release.gpu;" ::: "memory");
  flag_add(f);
}
__device__ __forceinline__ void l2_prefetch(const void* p, uint32_t bytes) { asm volatile("cp.async.bulk.prefetch.L2.global [%0], %1;" ::"l"(p), "r"(bytes) : "memory"); }
__device__ __forceinline__ void fence_async_smem() { asm volatile("fence.proxy.async.shared::cta;" ::: "memory"); }
__device__ __forceinline__ void bar_sync(int id, int n) { asm volatile("bar.sync %0, %1;" ::"r"(id), "r"(n) : "memory"); }
__device__ __forceinline__ void bar_arrive(int id, int n) { asm volatile("bar.arrive %0, %1;" ::"r"(id), "r"(n) : "memory"); }
__device__ __forceinline__ uint32_t lds32(uint32_t a) { uint32_t v; asm volatile("ld.shared.b32 %0, [%1];" : "=r"(v) : "r"(a) : "memory"); return v; }
__device__ __forceinline__ float2 lds64f(uint32_t a) { float2 v; asm volatile("ld.shared.v2.f32 {%0,%1}, [%2];" : "=f"(v.x), "=f"(v.y) : "r"(a) : "memory"); return v; }
__device__ __forceinline__ uint4 lds128(uint32_t a) { uint4 v; asm volatile("ld.shared.v4.b32 {%0,%1,%2,%3}, [%4];" : "=r"(v.x), "=r"(v.y), "=r"(v.z), "=r"(v.w) : "r"(a) : "memory"); return v; }
__device__ __forceinline__ float4 lds128f(uint32_t a) { float4 v; asm volatile("ld.shared.v4.f32 {%0,%1,%2,%3}, [%4];" : "=f"(v.x), "=f"(v.y), "=f"(v.z), "=f"(v.w) : "r"(a) : "memory"); return v; }
__device__ __forceinline__ void sts32(uint32_t a, uint32_t v) { asm volatile("st.shared.b32 [%0], %1;" ::"r"(a), "r"(v) : "memory"); }
__device__ __forceinline__ void sts64f(uint32_t a, float x, float y) { asm volatile("st.shared.v2.f32 [%0], {%1,%2};" ::"r"(a), "f"(x), "f"(y) : "memory"); }
__device__ __forceinline__ void sts128(uint32_t a, uint32_t x, uint32_t y, uint32_t z, uint32_t w) {
  asm volatile("st.shared.v4.b32 [%0], {%1,%2,%3,%4};" ::"r"(a), "r"(x), "r"(y), "r"(z), "r"(w) : "memory");
}
__device__ __forceinline__ void ldsm4(uint32_t (&r)[4], uint32_t a) {
  asm volatile("ldmatrix.sync.aligned.m8n8.x4.shared.b16 {%0,%1,%2,%3}, [%4];" : "=r"(r[0]), "=r"(r[1]), "=r"(r[2]), "=r"(r[3]) : "r"(a) : "memory");
}
__device__ __forceinline__ void stsm4t(uint32_t a, uint32_t r0, uint32_t r1, uint32_t r2, uint32_t r3) {
  asm volatile("stmatrix.sync.aligned.m8n8.x4.trans.shared.b16 [%0], {%1,%2,%3,%4};" ::"r"(a), "r"(r0), "r"(r1), "r"(r2), "r"(r3) : "memory");
}
__device__ __forceinline__ void stsm2t(uint32_t a, uint32_t r0, uint32_t r1) {
  asm volatile("stmatrix.sync.aligned.m8n8.x2.trans.shared.b16 [%0], {%1,%2};" ::"r"(a), "r"(r0), "r"(r1) : "memory");
}
__device__ __forceinline__ uint32_t pack_bf16(float lo, float hi) { uint32_t r; asm("cvt.rn.bf16x2.f32 %0, %1, %2;" : "=r"(r) : "f"(hi), "f"(lo)); return r; }
__device__ __forceinline__ float bf_lo(uint32_t v) { return __uint_as_float(v << 16); }
__device__ __forceinline__ float bf_hi(uint32_t v) { return __uint_as_float(v & 0xffff0000u); }
__device__ __forceinline__ uint32_t hfma2(uint32_t a, uint32_t b, uint32_t c) { uint32_t r; asm("fma.rn.bf16x2 %0, %1, %2, %3;" : "=r"(r) : "r"(a), "r"(b), "r"(c)); return r; }
__device__ __forceinline__ uint32_t hmul2(uint32_t a, uint32_t b) { uint32_t r; asm("mul.bf16x2 %0, %1, %2;" : "=r"(r) : "r"(a), "r"(b)); return r; }
__device__ __forceinline__ float gelu_half(float hz) {
  float u = hz * fmaf(hz * hz, 8.f * 0.044715f * 0.7978845608028654f, 2.f * 0.7978845608028654f);
  float t;
  asm("tanh.approx.f32 %0, %1;" : "=f"(t) : "f"(u));
  return fmaf(hz, t, hz);
}
__device__ __forceinline__ uint32_t gelu_pair(float hlo, float hhi) { return pack_bf16(gelu_half(hlo), gelu_half(hhi)); }
__device__ __forceinline__ uint64_t mkdesc(uint32_t addr, uint32_t lbo, uint32_t hi) { return (uint64_t)((addr >> 4) | ((lbo >> 4) << 16)) | ((uint64_t)hi << 32); }
#define WG_FENCE() asm volatile("wgmma.fence.sync.aligned;" ::: "memory")
#define WG_COMMIT() asm volatile("wgmma.commit_group.sync.aligned;" ::: "memory")
#define WG_WAIT(n) asm volatile("wgmma.wait_group.sync.aligned %0;" ::"n"(n) : "memory")
template <int N> __device__ __forceinline__ void reg_fence(float (&d)[N]) {
#pragma unroll
  for (int i = 0; i < N; i++) asm volatile("" : "+f"(d[i])::"memory");
}

__device__ __forceinline__ void wg_ss80n(float (&d)[40], uint64_t da, uint64_t db){
  asm volatile("wgmma.mma_async.sync.aligned.m64n80k16.f32.bf16.bf16 {%0,%1,%2,%3,%4,%5,%6,%7,%8,%9,%10,%11,%12,%13,%14,%15,%16,%17,%18,%19,%20,%21,%22,%23,%24,%25,%26,%27,%28,%29,%30,%31,%32,%33,%34,%35,%36,%37,%38,%39}, %40, %41, 1, 1, 1, 1, 1;"
   : "+f"(d[0]),"+f"(d[1]),"+f"(d[2]),"+f"(d[3]),"+f"(d[4]),"+f"(d[5]),"+f"(d[6]),"+f"(d[7]),"+f"(d[8]),"+f"(d[9]),"+f"(d[10]),"+f"(d[11]),"+f"(d[12]),"+f"(d[13]),"+f"(d[14]),"+f"(d[15]),"+f"(d[16]),"+f"(d[17]),"+f"(d[18]),"+f"(d[19]),"+f"(d[20]),"+f"(d[21]),"+f"(d[22]),"+f"(d[23]),"+f"(d[24]),"+f"(d[25]),"+f"(d[26]),"+f"(d[27]),"+f"(d[28]),"+f"(d[29]),"+f"(d[30]),"+f"(d[31]),"+f"(d[32]),"+f"(d[33]),"+f"(d[34]),"+f"(d[35]),"+f"(d[36]),"+f"(d[37]),"+f"(d[38]),"+f"(d[39])
   : "l"(da), "l"(db));
}
__device__ __forceinline__ void wg_ss80k(float (&d)[40], uint64_t da, uint64_t db){
  asm volatile("wgmma.mma_async.sync.aligned.m64n80k16.f32.bf16.bf16 {%0,%1,%2,%3,%4,%5,%6,%7,%8,%9,%10,%11,%12,%13,%14,%15,%16,%17,%18,%19,%20,%21,%22,%23,%24,%25,%26,%27,%28,%29,%30,%31,%32,%33,%34,%35,%36,%37,%38,%39}, %40, %41, 1, 1, 1, 1, 0;"
   : "+f"(d[0]),"+f"(d[1]),"+f"(d[2]),"+f"(d[3]),"+f"(d[4]),"+f"(d[5]),"+f"(d[6]),"+f"(d[7]),"+f"(d[8]),"+f"(d[9]),"+f"(d[10]),"+f"(d[11]),"+f"(d[12]),"+f"(d[13]),"+f"(d[14]),"+f"(d[15]),"+f"(d[16]),"+f"(d[17]),"+f"(d[18]),"+f"(d[19]),"+f"(d[20]),"+f"(d[21]),"+f"(d[22]),"+f"(d[23]),"+f"(d[24]),"+f"(d[25]),"+f"(d[26]),"+f"(d[27]),"+f"(d[28]),"+f"(d[29]),"+f"(d[30]),"+f"(d[31]),"+f"(d[32]),"+f"(d[33]),"+f"(d[34]),"+f"(d[35]),"+f"(d[36]),"+f"(d[37]),"+f"(d[38]),"+f"(d[39])
   : "l"(da), "l"(db));
}
__device__ __forceinline__ void wg_ss152k(float (&d)[76], uint64_t da, uint64_t db){
  asm volatile("wgmma.mma_async.sync.aligned.m64n152k16.f32.bf16.bf16 {%0,%1,%2,%3,%4,%5,%6,%7,%8,%9,%10,%11,%12,%13,%14,%15,%16,%17,%18,%19,%20,%21,%22,%23,%24,%25,%26,%27,%28,%29,%30,%31,%32,%33,%34,%35,%36,%37,%38,%39,%40,%41,%42,%43,%44,%45,%46,%47,%48,%49,%50,%51,%52,%53,%54,%55,%56,%57,%58,%59,%60,%61,%62,%63,%64,%65,%66,%67,%68,%69,%70,%71,%72,%73,%74,%75}, %76, %77, 1, 1, 1, 1, 0;"
   : "+f"(d[0]),"+f"(d[1]),"+f"(d[2]),"+f"(d[3]),"+f"(d[4]),"+f"(d[5]),"+f"(d[6]),"+f"(d[7]),"+f"(d[8]),"+f"(d[9]),"+f"(d[10]),"+f"(d[11]),"+f"(d[12]),"+f"(d[13]),"+f"(d[14]),"+f"(d[15]),"+f"(d[16]),"+f"(d[17]),"+f"(d[18]),"+f"(d[19]),"+f"(d[20]),"+f"(d[21]),"+f"(d[22]),"+f"(d[23]),"+f"(d[24]),"+f"(d[25]),"+f"(d[26]),"+f"(d[27]),"+f"(d[28]),"+f"(d[29]),"+f"(d[30]),"+f"(d[31]),"+f"(d[32]),"+f"(d[33]),"+f"(d[34]),"+f"(d[35]),"+f"(d[36]),"+f"(d[37]),"+f"(d[38]),"+f"(d[39]),"+f"(d[40]),"+f"(d[41]),"+f"(d[42]),"+f"(d[43]),"+f"(d[44]),"+f"(d[45]),"+f"(d[46]),"+f"(d[47]),"+f"(d[48]),"+f"(d[49]),"+f"(d[50]),"+f"(d[51]),"+f"(d[52]),"+f"(d[53]),"+f"(d[54]),"+f"(d[55]),"+f"(d[56]),"+f"(d[57]),"+f"(d[58]),"+f"(d[59]),"+f"(d[60]),"+f"(d[61]),"+f"(d[62]),"+f"(d[63]),"+f"(d[64]),"+f"(d[65]),"+f"(d[66]),"+f"(d[67]),"+f"(d[68]),"+f"(d[69]),"+f"(d[70]),"+f"(d[71]),"+f"(d[72]),"+f"(d[73]),"+f"(d[74]),"+f"(d[75])
   : "l"(da), "l"(db));
}
__device__ __forceinline__ void wg_rs64(float (&d)[32], const uint32_t (&a)[4], uint64_t db, int sd){
  asm volatile("{.reg .pred p; setp.ne.b32 p, %37, 0;\n"
   "wgmma.mma_async.sync.aligned.m64n64k16.f32.bf16.bf16 {%0,%1,%2,%3,%4,%5,%6,%7,%8,%9,%10,%11,%12,%13,%14,%15,%16,%17,%18,%19,%20,%21,%22,%23,%24,%25,%26,%27,%28,%29,%30,%31}, {%32,%33,%34,%35}, %36, p, 1, 1, 0;}"
   : "+f"(d[0]),"+f"(d[1]),"+f"(d[2]),"+f"(d[3]),"+f"(d[4]),"+f"(d[5]),"+f"(d[6]),"+f"(d[7]),"+f"(d[8]),"+f"(d[9]),"+f"(d[10]),"+f"(d[11]),"+f"(d[12]),"+f"(d[13]),"+f"(d[14]),"+f"(d[15]),"+f"(d[16]),"+f"(d[17]),"+f"(d[18]),"+f"(d[19]),"+f"(d[20]),"+f"(d[21]),"+f"(d[22]),"+f"(d[23]),"+f"(d[24]),"+f"(d[25]),"+f"(d[26]),"+f"(d[27]),"+f"(d[28]),"+f"(d[29]),"+f"(d[30]),"+f"(d[31])
   : "r"(a[0]),"r"(a[1]),"r"(a[2]),"r"(a[3]), "l"(db), "r"(sd));
}

template <int J, int Q0, int Q1> __device__ __forceinline__ void conv_mma(float (&d)[32], const uint32_t (&A)[16][4], uint64_t db) {
#pragma unroll
  for (int q = Q0; q <= Q1; q++)
#pragma unroll
    for (int s = 0; s < 4; s++) wg_rs64(d, A[4 * q + s], db + ((1024 * (J - q) - 32 * s) >> 4), (q | s) != 0);
}
template <int J>
__device__ __forceinline__ void conv_drain(float (&d)[32], float& c0, float& c1, uint32_t ex, uint32_t qc, uint32_t hst, int wg, int w, int lane) {
  reg_fence(d);
  float z[4] = {d[0] + c0, d[1] + c1, d[4] + d[2], d[5] + d[3]};
#pragma unroll
  for (int pp = 1; pp < 4; pp++)
    if (J < 3 || w + pp < 4)
      sts64f(ex + w * 768 + (J & 1) * 3072 + (pp - 1) * 256, __uint_as_float(pack_bf16(d[8 * pp] + d[8 * pp - 2], d[8 * pp + 1] + d[8 * pp - 1])),
             __uint_as_float(pack_bf16(d[8 * pp + 4] + d[8 * pp + 2], d[8 * pp + 5] + d[8 * pp + 3])));
  asm volatile("mov.b32 %0,%1;" : "=f"(c0) : "f"(d[30]));
  asm volatile("mov.b32 %0,%1;" : "=f"(c1) : "f"(d[31]));
  uint32_t v0[2], v1[2];
#pragma unroll
  for (int jj = 0; jj < 2; jj++) { v0[jj] = lds32(qc + (8 * J + jj) * 256); v1[jj] = lds32((qc ^ 32) + (8 * J + jj) * 256); }
  bar_sync(1 + wg, 128);
#pragma unroll
  for (int pp = 1; pp < 4; pp++) {
    const bool later = pp > w;
    if (J > 0 || !later) {
      const float2 u = lds64f(ex + ((w - pp) & 3) * 768 + (pp - 1) * 256 + (((J & 1) != 0) != later ? 3072 : 0));
      z[0] += bf_lo(__float_as_uint(u.x)); z[1] += bf_hi(__float_as_uint(u.x)); z[2] += bf_lo(__float_as_uint(u.y)); z[3] += bf_hi(__float_as_uint(u.y));
    }
  }
  const bool p = lane & 4, sw = lane & 2;
#pragma unroll
  for (int jj = 0; jj < 2; jj++) {
    const float recv = __shfl_xor_sync(0xffffffffu, p ? z[2 * jj] : z[2 * jj + 1], 4), keep = p ? z[2 * jj + 1] : z[2 * jj];
    const float ylo = p ? recv : keep, yhi = p ? keep : recv;
    const uint32_t qv = sw ? v1[jj] : v0[jj], cv = sw ? v0[jj] : v1[jj];
    sts32(hst + (8 * J + jj) * 128, pack_bf16(fmaf(bf_lo(qv), ylo, bf_lo(cv)), fmaf(bf_hi(qv), yhi, bf_hi(cv))));
  }
}
template <int I0> __device__ __forceinline__ void conv_load_a(uint32_t (&A)[16][4], uint32_t ta) {
#pragma unroll
  for (int i = I0; i < I0 + 8; i++) {
    const uint32_t a = ta - (i >> 2) * 1024 - (i & 3) * 32;
    A[i][0] = lds32(a); A[i][1] = lds32(a - 128); A[i][2] = lds32(a + 16); A[i][3] = lds32(a - 112);
  }
}

template <int KIND, int KS, int NWP, uint32_t WB, int WF, int WE, int RW, int NX, uint32_t XB, int XE, int NACC>
__device__ __forceinline__ void gemm_seg(float (&d)[NACC], uint32_t sb, int nch, uint32_t woff, uint32_t wi, uint32_t wmask, uint32_t xmask, bool waitx,
                                         int lt, int tok_arrive) {
  const uint32_t bars = sb + BARS;
  const uint64_t la0 = mkdesc(sb + WR + woff, 1024, 0x40000040), lb0 = KIND == 0 ? mkdesc(sb + XR, 256, 0xC0000050) : mkdesc(sb + XR, 16, 0x40000040);
  uint32_t xi = 0, pw = 0, px = 0;
  uint32_t bw = bars + 8 * WF + 8 * wi, bx = bars + 8 * B_XF;
  constexpr bool RX = KIND == 1 || KIND == 2;
  if (waitx) mbar_wait2(bx, xmask & 1, bw, (wmask >> wi) & 1); else mbar_wait(bw, (wmask >> wi) & 1);
  reg_fence(d);
#pragma unroll 1
  for (int c = nch; c > 0; c--) {
    const uint64_t la = la0 + wi * (WB >> 4), lb = lb0 + xi * (XB >> 4);
    WG_FENCE();
#pragma unroll
    for (int k = 0; k < KS; k++) {
      if constexpr (KIND == 0) wg_ss80n(d, la + k * 128, lb + k * 160);
      else if constexpr (KIND == 1 || KIND == 3) wg_ss80k(d, la + k * 128, lb + (k >> 2) * 640 + (k & 3) * 2);
      else wg_ss152k(d, la + k * 128, lb + k * 2);
    }
    WG_COMMIT();
    const uint32_t rw = bw + 8 * (WE - WF), rx = bx + 8 * (XE - B_XF);
    wmask ^= 1u << wi;
    wi = wi + 1 == NWP ? 0 : wi + 1;
    if (KIND == 3) xi = xi + 1 == NX ? 0 : xi + 1;
    else if (KIND != 0) { xmask ^= 1u << xi; xi = xi + 1 == NX ? 0 : xi + 1; }
    else xi++;
    bw = bars + 8 * WF + 8 * wi; bx = bars + 8 * B_XF + 8 * (KIND == 0 ? xi >> 1 : xi);
    if (KIND == 0) waitx = !(xi & 1);
    if (KIND == 0 && xi == 8) bar_sync(7, 352);
    if (c == 1 && tok_arrive >= 0) bar_arrive(tok_arrive, 256);
    WG_WAIT(1);
    if (lt < RW && pw) { mbar_arrive(pw); if (RX && lt == 0) mbar_arrive(px); }
    if (c > 1) { if (waitx) mbar_wait2(bx, (xmask >> xi) & 1, bw, (wmask >> wi) & 1); else mbar_wait(bw, (wmask >> wi) & 1); }
    pw = rw; px = rx;
  }
  WG_WAIT(0);
  reg_fence(d);
  if (lt < RW) { mbar_arrive(pw); if (RX && lt == 0) mbar_arrive(px); }
}

__device__ __forceinline__ void pre_unit(uint32_t sb, int r, int j, int lane, float2 st0, float2 st1) {
  const int m_ = lane >> 3, rho = lane & 7, t = lane & 3;
  const uint32_t col = (j & 3) * 32 + (m_ >> 1) * 16, row = (m_ & 1) * 8 + rho;
  const uint32_t ka = sb + PK + r * 9216 + ((j >> 2) * 19 + row) * 128 + col;
  uint32_t k0[4], k1[4], k2[4], k3[4], vv[4], xx[4];
  ldsm4(k3, swz128(ka)); ldsm4(k2, swz128(ka + 128)); ldsm4(k1, swz128(ka + 256)); ldsm4(k0, swz128(ka + 384));
  ldsm4(vv, swz128(sb + PK + r * 9216 + 5120 + ((j >> 2) * 16 + row) * 128 + col));
  ldsm4(xx, swz128(sb + PX + ((2 * r + (j >> 2)) * 16 + row) * 128 + col));
  uint32_t kvr[4], qr[4], cr[4];
#pragma unroll
  for (int oc = 0; oc < 2; oc++) {
    const int ch = 128 * r + 16 * j + 8 * oc + 2 * t;
    const uint4 v = lds128(sb + PSK + ch * 8);
    const uint32_t dd = lds32(sb + PSK + 5120 + ch * 2);
    const uint32_t w0 = __byte_perm(v.x, v.z, 0x5410), w1 = __byte_perm(v.x, v.z, 0x7632), w2 = __byte_perm(v.y, v.w, 0x5410), w3 = __byte_perm(v.y, v.w, 0x7632);
#pragma unroll
    for (int th = 0; th < 2; th++) {
      const int m = 2 * oc + th;
      uint32_t ks = hmul2(k3[m], w3);
      ks = hfma2(k2[m], w2, ks);
      ks = hfma2(k1[m], w1, ks);
      ks = hfma2(k0[m], w0, ks);
      kvr[m] = hmul2(ks, vv[m]);
      const float mm = th ? st1.x : st0.x, rr = th ? st1.y : st0.y;
      const float xl = bf_lo(xx[m]), xh = bf_hi(xx[m]);
      const float ql = (xl - mm) * rr, qh = (xh - mm) * rr;
      qr[m] = pack_bf16(ql, qh);
      cr[m] = pack_bf16(fmaf(ql * bf_lo(dd), bf_lo(kvr[m]), xl), fmaf(qh * bf_hi(dd), bf_hi(kvr[m]), xh));
    }
  }
  const int ch = 16 * j + 8 * (m_ >> 1) + rho, th = m_ & 1;
  stsm4t(sb + EXCH + 12288 + r * 4096 + ch * 32 + ((th ^ ((ch >> 2) & 1)) << 4), kvr[0], kvr[1], kvr[2], kvr[3]);
  const uint32_t qa = sb + QCB(r) + ch * 64;
  const int sx = (ch >> 1) & 3;
  stsm4t(qa + ((th ^ sx) << 4), qr[0], qr[1], qr[2], qr[3]);
  stsm4t(qa + (((2 + th) ^ sx) << 4), cr[0], cr[1], cr[2], cr[3]);
}
__device__ __forceinline__ void build_table(uint32_t sb, int r, int lt) {
  const uint32_t tb = sb + TABB(r), raw = sb + RAWB(r);
#pragma unroll
  for (int i = 0; i < 2; i++) {
    const int s = lt + 128 * i;
    const uint4 v = lds128(raw + s * 16);
    uint32_t pv = lds32(raw + s * 16 - 4);
    if (i == 0) pv = s == 0 ? 0u : pv;
    sts128(tb + TAB_O + (1020 - 4 * s) * 4, __byte_perm(v.w, 0, 0x1032), __byte_perm(v.z, 0, 0x1032), __byte_perm(v.y, 0, 0x1032), __byte_perm(v.x, 0, 0x1032));
    sts128(tb + TAB_E + (1021 - 4 * s) * 4, __byte_perm(v.w, v.z, 0x7610), __byte_perm(v.z, v.y, 0x7610), __byte_perm(v.y, v.x, 0x7610), __byte_perm(v.x, pv, 0x7610));
  }
  if (lt < 7) sts32(tb + (lt < 3 ? TAB_E + (1025 + lt) * 4 : TAB_O + (1021 + lt) * 4), 0);
}
__device__ __forceinline__ void warp_signal(uint32_t bar, int lane) {
  fence_async_smem();
  __syncwarp();
  if (lane == 0) mbar_arrive(bar);
}

__device__ __forceinline__ void filter_load(const Params& p, uint32_t sb, int b, int r) {
  mbar_expect(sb + BARS + 8 * (B_F + r), 4096);
  bulk_load(sb + RAWB(r), p.ssm_k + (size_t)(128 * r + b) * S_, 4096, sb + BARS + 8 * (B_F + r));
}
__device__ __forceinline__ void front_load(const Params& p, uint32_t sb, int b, int r) {
  const uint32_t bars = sb + BARS;
  mbar_expect(bars + 8 * (B_KV + r), 4864 + 4096);
  tma_load3(sb + PK + r * 9216, &p.kin, 0, 16 * b - 3, 2 * r, bars + 8 * (B_KV + r));
  tma_load3(sb + PK + r * 9216 + 5120, &p.vin, 0, 16 * b, 2 * r, bars + 8 * (B_KV + r));
  if (r < 2) filter_load(p, sb, b, r);
}

__global__ void __launch_bounds__(NTHR, 1) fused_kernel(const __grid_constant__ Params p) {
  extern __shared__ __align__(1024) uint8_t smem_raw[];
  const uint32_t sb = (uint32_t)__cvta_generic_to_shared(smem_raw);
  const int tid = threadIdx.x, lane = tid & 31;
  const int warp = __shfl_sync(0xffffffffu, tid >> 5, 0);
  const int wg = warp >> 2;
  const int b = blockIdx.x;
  const uint32_t bars = sb + BARS;
  if (warp >= 12) {
    if (warp == 13 && b >= 128 && elect()) mbar_init(bars + 8 * B_X, 1);
    if (warp < 14 && b < 128 && elect()) {
      if (warp == 13) {
        mbar_init(bars + 8 * B_X, 1);
        mbar_expect(bars + 8 * B_X, 20480 + 5120 + 1280);
        tma_load3(sb + PX, &p.xin, 0, 16 * b, 0, bars + 8 * B_X);
        bulk_load(sb + PSK, p.shift_k, 5120, bars + 8 * B_X);
        bulk_load(sb + PSK + 5120, p.ssm_D, 1280, bars + 8 * B_X);
      }
#pragma unroll 1
      for (int r = warp - 12; r < 5; r += 2) { mbar_init(bars + 8 * (B_KV + r), 1); mbar_init(bars + 8 * (B_F + r), 1); front_load(p, sb, b, r); }
    }
  } else {
    const int i = B_U + warp + 12 * lane;
    if (i < B_NUM) {
      uint32_t cnt = 1;
      if (i >= B_PST && i < B_HST) cnt = 8;
      else if ((i >= B_HST && i < B_HDONE) || (i >= B_SG && i < B_SD) || i >= B_SS2 || i == B_SS3 || i == B_SS3 + 1 || (i >= B_SS && i < B_WF1)) cnt = 4;
      else if (i == B_XFREE) cnt = 6;
      else if (i == B_TOK) cnt = 4;
      else if ( (i >= B_X3E && i < B_WF4) || (i >= B_WE3 && i < B_XF)) cnt = 3;
      else if ((i >= B_XE && i < B_X3E) || (i >= B_WE2 && i < B_WF3) || (i >= B_WF4 && i < B_STRAW)) cnt = 2;
      mbar_init(bars + 8 * i, cnt);
    }
  }
  if (tid < 40 && b < 128) sts128(sb + UB(tid >> 3) + (tid & 7) * 16, 0, 0, 0, 0);
  asm volatile("{.reg .pred p; setp.ne.u32 p, %0, 0; @p trap;}" ::"r"(sb & 1023));
  __syncthreads();

  const int ti = b / 5, fj = b % 5;
  const int t3 = (b / 3) % 14, f3 = b / 42 * 3 + b % 3;

  if (wg == 3) {
    asm volatile("setmaxnreg.dec.sync.aligned.u32 32;");
    if (warp == 13 && b >= 128) {
      unsigned ep;
      asm volatile("ld.relaxed.gpu.global.u32 %0, [%1];" : "=r"(ep) : "l"(&g_epoch) : "memory");
      poll1(&g_flag[F_P * 32], (ep + 1) * 128u);
      if (elect()) {
        mbar_expect(bars + 8 * B_X, 204800);
        bulk_load(sb, p.pw1 + (b - 128) * 160 * D_, 102400, bars + 8 * B_X);
        bulk_load(sb + 102400, p.pw1 + ((b - 128) * 160 + 80) * D_, 102400, bars + 8 * B_X);
      }
    }
    if (b < 130) {
      if (warp == 12) {
        if (b < 128) {
          mbar_wait(bars + 8 * (B_QC + 1), 0);
          if (elect()) {
            l2_prefetch(reinterpret_cast<const uint8_t*>(p.pw1) + b * 6400, 6400);
            l2_prefetch(reinterpret_cast<const uint8_t*>(p.pw2) + b * 6400, 6400);
            l2_prefetch(reinterpret_cast<const uint8_t*>(p.pw3) + b * 17280, 17280);
            l2_prefetch(reinterpret_cast<const uint8_t*>(p.pw4) + b * 17280, 17280);
          }
          mbar_wait(bars + 8 * B_HDONE, 0);
          mbar_wait(bars + 8 * (B_TAB + 4), 0);
        } else {
          mbar_wait(bars + 8 * B_CS, 0);
        }
#pragma unroll 1
        for (int n = 0; n < 20; n++) {
          const uint32_t q = n & 3;
          mbar_wait(bars + 8 * (B_WE2 + q), ((n >> 2) & 1) ^ 1);
          if (elect()) {
            mbar_expect(bars + 8 * (B_WF2 + q), 16384);
            if (n < 10) tma_load3(sb + WR + q * 16384, &p.w1p, 0, 64 * n, 2 * fj, bars + 8 * (B_WF2 + q));
            else tma_load2(sb + WR + q * 16384, &p.w2d, 128 * fj + (n < 15 ? 0 : 64), 128 * (n < 15 ? n - 10 : n - 15), bars + 8 * (B_WF2 + q));
          }
        }
        if (b < 126) {
#pragma unroll 1
          for (int i = 0; i < 5; i++) {
            const uint32_t q = i < 3 ? i : i - 3;
            mbar_wait(bars + 8 * (i < 3 ? B_WE2 + 1 + i : B_WE3 + q), 0);
            if (elect()) { mbar_expect(bars + 8 * (B_WF3 + q), 24576); tma_load3(sb + WR + q * 24576, &p.w3t, 0, 128 * i, 3 * f3, bars + 8 * (B_WF3 + q)); }
          }
          int k = 64, f = 192 * f3;
          uint32_t s = 6;
#pragma unroll 1
          for (int j = 0; j < 15; j++) {
            mbar_wait(bars + 8 * (j < 3 ? B_WE3 + 2 : j < 6 ? B_WE3 : j < 9 ? B_WE3 + 1 : B_WE1 + s), j >= 3 && j < 9);
            if (elect()) { mbar_expect(bars + 8 * (B_WF1 + s), 8192); tma_load2(sb + WR + s * 8192, &p.w3, f, k, bars + 8 * (B_WF1 + s)); }
            k += 128;
            if (k == 704) { k = 64; f += 64; }
            if (++s == 9) s = 0;
          }
        }
        {
          int k = 0;
          uint32_t q = 4, par = 1;
#pragma unroll 1
          for (int i = 0; i < 27; i++) {
            if (i >= 6) mbar_wait(bars + 8 * (B_WE4 + q), par);
            else if (b >= 126) { if (i == 0) { mbar_wait(bars + 8 * (B_WE2 + 3), 0); mbar_wait(bars + 8 * (B_XE + 4), 0); } }
            else if (i < 2 || i >= 4) mbar_wait(bars + 8 * (B_WE1 + ((0x210075u >> (4 * i)) & 15u)), i >= 1);
            else if (i == 2) mbar_wait(bars + 8 * (B_X3E + 4), 1);
            if (elect()) {
              mbar_expect(bars + 8 * (B_WF4 + q), 16384);
              tma_load3(sb + WR - 32768 + q * 16384, &p.w4p, 0, k, 2 * fj, bars + 8 * (B_WF4 + q));
            }
            k += 192;
            if (k >= F_) k -= F_ - 64;
            if (++q == 6) q = 0;
            if (q == 4) par ^= 1;
          }
        }
      } else if (warp == 13) {
        unsigned ep;
        asm volatile("ld.relaxed.gpu.global.u32 %0, [%1];" : "=r"(ep) : "l"(&g_epoch) : "memory");
        ep += 1;
        if (lane < 5) mbar_expect(bars + 8 * (B_XF + lane), 20480);
        __syncwarp();
        if (b < 128) {
          if (lane < 10) mbar_expect(bars + 8 * (B_U + lane), lane < 5 ? 4096 : 8192);
          __syncwarp();
          poll1(&g_flag[F_P * 32], ep * 128u);
          __syncwarp();
#pragma unroll 1
          for (int r = 0; r < 5; r++) {
            if (elect()) {
              const int c = 128 * r + b;
              bulk_load(sb + UB(r) + 128, g_kvT + (size_t)c * S_, 4096, bars + 8 * (B_U + r));
              bulk_load(sb + QCB(r), g_qc + (size_t)c * S_ * 2, 8192, bars + 8 * (B_QC + r));
            }
          }
        } else {
          mbar_wait(bars + 8 * B_CS, 0);
        }
#pragma unroll 1
        for (int r = 0; r < 5; r++) {
          if (b < 128) mbar_wait(bars + 8 * (B_HDONE + r), 0);
          poll1(&g_flag[(F_C + r) * 32], ep * (r == 3 ? 132u : 128u));
          if (elect()) {
            bulk_load(sb + XR + r * 20480, g_hT + (size_t)ti * (D_ * TT) + r * 10240, 20480, bars + 8 * (B_XF + r));
          }
        }
        mbar_wait(bars + 8 * B_XFREE, 0);
        if (lane < 5) mbar_expect(bars + 8 * (B_XF + lane), 20480);
        __syncwarp();
        poll3(&g_flag[(F_1 + max(ti - 1, 0)) * 32], &g_flag[(F_1 + ti) * 32], &g_flag[(F_1 + min(ti + 1, 25)) * 32], ep * 10u);
#pragma unroll 1
        for (int i = 0; i < 5; i++) {
          if (elect()) {
            tma_load3(sb + XR + i * 20480, &p.hsL, 0, TT * ti, 2 * i, bars + 8 * (B_XF + i));
          }
        }
        if (b < 126) {
          const int t0 = (TT3 * t3) / TT, t2 = min((TT3 * t3 + TT3 - 1) / TT, 25);
#pragma unroll 1
          for (int h = 0; h < 2; h++) {
            poll3(&g_flag[(F_2 + 2 * t0 + h) * 32], &g_flag[(F_2 + 2 * (t0 + 1) + h) * 32], &g_flag[(F_2 + 2 * t2 + h) * 32], ep * 5u);
            __syncwarp();
#pragma unroll 1
            for (int s = 0; s < 5; s++) {
              mbar_wait(bars + 8 * ((h ? B_X3E : B_XE) + s), 0);
              if (elect()) {
                mbar_expect(bars + 8 * (B_XF + s), TT3 * 128);
                tma_load2(sb + XR + s * 19456, &p.x1L, 128 * s + 64 * h, TT3 * t3, bars + 8 * (B_XF + s));
              }
            }
          }
        }
        {
          uint32_t s = 0, q = 4, par = 1;
          if (b >= 126) mbar_wait(bars + 8 * (B_XE + 4), 0);
#pragma unroll 1
          for (int cl = 0; cl < 3; cl++) {
            poll1(&g_flag[(F_3 + cl) * 32], ep * 126u);
            __syncwarp();
#pragma unroll 1
            for (int k = 64 * cl; k < F_; k += 192) {
              if (cl || k >= 6 * 192) mbar_wait(bars + 8 * (B_WE4 + q), par);
              else if (b < 126) mbar_wait(bars + 8 * (B_X3E + ((s + 1) >> 1)), 1);
              if (elect()) {
                mbar_expect(bars + 8 * (B_WF4 + q), 10240);
                tma_load2(sb + XR + s * 10240, &p.HL, k, TT * ti, bars + 8 * (B_WF4 + q));
              }
              if (++q == 6) q = 0;
              if (++s == 6) { s = 0; par ^= 1; }
            }
          }
        }
        if (b == 0 && lane == 0) asm volatile("st.relaxed.gpu.global.u32 [%0], %1;" ::"l"(&g_epoch), "r"(ep) : "memory");
      } else {
        const int sw = warp - 14;
        if (sw && lane < 20) asm volatile("prefetch.tensormap [%0];" ::"l"(&p.w1p + lane) : "memory");
        __syncwarp();
        if (b < 128) {
          if (!sw) {
#pragma unroll 1
            for (int r = 0; r < 5; r++) {
              mbar_wait(bars + 8 * (B_PST + r), 0);
              if (elect()) {
                tma_store2(&p.kvT, 16 * b, 128 * r, sb + EXCH + 12288 + r * 4096);
                tma_store2(&p.qc, 32 * b, 128 * r, sb + QCB(r));
              }
              __syncwarp();
            }
            if (elect()) {
              store_commit_wait();
              flag_release(&g_flag[F_P * 32]);
#pragma unroll 1
              for (int r = 2; r < 5; r++) filter_load(p, sb, b, r);
            }
            __syncwarp();
          }
          {
#pragma unroll 1
            for (int r = sw; r < 5; r += 2) {
              mbar_wait(bars + 8 * (B_HST + r), 0);
              if (elect()) {
                const int ch = 128 * r + b;
                tma_store5(&p.hT, 0, ch & 7, 0, ch >> 3, 0, sb + TABB(r));
                store_commit_wait();
                mbar_arrive(bars + 8 * (B_HDONE + r));
                flag_release(&g_flag[(F_C + r) * 32]);
              }
              __syncwarp();
            }
          }
        }
        const uint32_t stg = sb + GST + sw * 19456;
        const int fa = 128 * fj + 64 * sw, ga = fa / 160, gb = (fa + 32) / 160;
        const int ra = TT * ti + ((0x0413 >> (4 * ga)) & 15), rb = TT * ti + ((0x0413 >> (4 * gb)) & 15);
#pragma unroll 1
        for (int part = 0; part < 2; part++) {
          mbar_wait(bars + 8 * ((part ? B_SS3 : B_SS2) + sw), 0);
          if (elect()) {
            tma_store2(&p.hsS, fa, ra + 32 * part, stg + 2048 * part);
            tma_store2(&p.hsS, fa + 32, rb + 32 * part, stg + 5120 + 2048 * part);
          }
          __syncwarp();
        }
        mbar_wait(bars + 8 * (B_SG + sw), 0);
        if (elect()) {
          tma_store2(&p.hsS2, fa, ra + 64, stg + 4096);
          tma_store2(&p.hsS2, fa + 32, rb + 64, stg + 5120 + 4096);
          store_commit_wait();
          mbar_arrive(bars + 8 * (B_SD + sw));
          flag_release(&g_flag[(F_1 + ti) * 32]);
        }
        __syncwarp();
        mbar_wait(bars + 8 * (B_SG + sw), 1);
        if (elect()) {
          tma_store2(&p.x1S, 128 * fj + 64 * sw, TT * ti, stg);
          if (!sw) {
            store_commit_wait();
            mbar_arrive(bars + 8 * B_SD);
            flag_release(&g_flag[(F_2 + 2 * ti) * 32]);
          }
        }
        __syncwarp();
        mbar_wait(bars + 8 * (B_SS + sw), 0);
        if (elect()) {
          bulk_store(g_st + (2 * fj + sw) * 2176 + TT * ti, sb + XST + sw * 640, 640);
          store_commit_wait();
          if (sw) mbar_arrive(bars + 8 * (B_SD + 1));
          flag_release(&g_flag[(F_S + ti) * 32]);
          if (sw) { flag_add(&g_flag[(F_2 + 2 * ti + 1) * 32]); }
        }
        __syncwarp();
        if (b < 126) {
          if (sw) {
            unsigned ep;
            asm volatile("ld.relaxed.gpu.global.u32 %0, [%1];" : "=r"(ep) : "l"(&g_epoch) : "memory");
            poll3(&g_flag[(F_S + (TT3 * t3) / TT) * 32], &g_flag[(F_S + (TT3 * t3) / TT + 1) * 32], &g_flag[(F_S + min((TT3 * t3 + TT3 - 1) / TT, 25)) * 32], (ep + 1) * 10u);
            if (elect()) {
              mbar_expect(bars + 8 * B_STRAW, 10 * 1232);
              tma_load2(sb + STRAW, &p.stL, (TT3 * t3) & ~1, 0, bars + 8 * B_STRAW);
            }
            mbar_wait(bars + 8 * B_STRAW, 0);
#pragma unroll 1
            for (int r = lane; r < 152; r += 32) {
              float s = 0.f, ss = 0.f;
#pragma unroll
              for (int i = 0; i < 10; i++) { const float2 v = lds64f(sb + STRAW + i * 1232 + (r + (t3 & 1)) * 8); s += v.x; ss += v.y; }
              const float m = s * (1.f / D_);
              const float rs = 0.5f * rsqrtf(fmaxf(ss * (1.f / D_) - m * m, 0.f) + EPS);
              sts64f(sb + ST3 + r * 8, rs, -m * rs);
            }
            __syncwarp();
            if (lane == 0) { mbar_arrive(bars + 8 * B_ST3); }
            __syncwarp();
          }
#pragma unroll 1
          for (int w = sw; w < 3; w += 2) {
            mbar_wait(bars + 8 * (B_SS2 + w), w < 2);
            if (elect()) tma_store2(&p.HL, 192 * f3 + 64 * w, TT3 * t3, stg);
            __syncwarp();
            mbar_wait(bars + 8 * (B_SG + w), 0);
            if (elect()) {
              tma_store2(&p.HS, 192 * f3 + 64 * w, TT3 * t3 + TT, stg + 10240);
              store_commit_wait();
              mbar_arrive(bars + 8 * (B_SD + w));
              flag_release(&g_flag[(F_3 + w) * 32]);
            }
            __syncwarp();
          }
        }
        mbar_wait(bars + 8 * (B_SG + sw), b < 126);
        if (elect()) {
          tma_store2(&p.outS, 128 * fj + 64 * sw, TT * ti, stg);
          store_commit_wait();
        }
      }
    }
    __syncwarp();
  } else {
    asm volatile("setmaxnreg.inc.sync.aligned.u32 160;");
    const int w = warp & 3, g = lane >> 2, lt = tid & 127;
    const bool lead = lt == 0;
    if (b >= 128) {
      mbar_wait(bars + 8 * B_X, 0);
      if (tid < 320) {
        float a0 = 0.f, a1 = 0.f;
#pragma unroll 16
        for (int r = 0; r < 160; r++) { const uint32_t v = lds32(sb + r * 1280 + tid * 4); a0 += bf_lo(v); a1 += bf_hi(v); }
        reinterpret_cast<float2*>(g_cs1)[(b - 128) * 320 + tid] = make_float2(a0, a1);
        if (b == 131 && tid < 60) {
          reinterpret_cast<uint4*>(g_hs + (2 + (tid >= 40)) * D_ + (tid >= 20 ? 320 : 0))[tid % 20] = make_uint4(0, 0, 0, 0);
          asm volatile("fence.proxy.async.global;" ::: "memory");
        }
        __threadfence();
      }
      bar_sync(7, 384);
      if (tid == 0) { flag_add(&g_flag[(F_C + 3) * 32]); mbar_arrive(bars + 8 * B_CS); }
    } else {
      mbar_wait(bars + 8 * B_X, 0);
      if (warp < 8) {
        const int row = 2 * warp + (lane >> 4);
        float xv[40];
#pragma unroll
        for (int i = 0; i < 5; i++) {
          uint4 v = lds128(sb + PX + ((2 * i + ((lane >> 3) & 1)) * 16 + row) * 128 + (lane & 7) * 16);
          xv[8 * i] = bf_lo(v.x); xv[8 * i + 1] = bf_hi(v.x); xv[8 * i + 2] = bf_lo(v.y); xv[8 * i + 3] = bf_hi(v.y);
          xv[8 * i + 4] = bf_lo(v.z); xv[8 * i + 5] = bf_hi(v.z); xv[8 * i + 6] = bf_lo(v.w); xv[8 * i + 7] = bf_hi(v.w);
        }
        float s0 = 0.f, s1 = 0.f, s2 = 0.f, s3 = 0.f;
#pragma unroll
        for (int i = 0; i < 40; i += 4) { s0 += xv[i]; s1 += xv[i + 1]; s2 += xv[i + 2]; s3 += xv[i + 3]; }
        float s = (s0 + s1) + (s2 + s3);
#pragma unroll
        for (int o = 8; o; o >>= 1) s += __shfl_xor_sync(0xffffffffu, s, o);
        const float m = s * (1.f / D_);
        s0 = s1 = s2 = s3 = 0.f;
#pragma unroll
        for (int i = 0; i < 40; i += 4) {
          const float a0 = xv[i] - m, a1 = xv[i + 1] - m, a2 = xv[i + 2] - m, a3 = xv[i + 3] - m;
          s0 = fmaf(a0, a0, s0); s1 = fmaf(a1, a1, s1); s2 = fmaf(a2, a2, s2); s3 = fmaf(a3, a3, s3);
        }
        s = (s0 + s1) + (s2 + s3);
#pragma unroll
        for (int o = 8; o; o >>= 1) s += __shfl_xor_sync(0xffffffffu, s, o);
        if ((lane & 15) == 0) sts64f(sb + ROWST + row * 8, m, rsqrtf(s * (1.f / D_) + EPS));
      }
      bar_sync(7, 384);
      {
        const float2 st0 = lds64f(sb + ROWST + g * 8), st1 = lds64f(sb + ROWST + (8 + g) * 8);
#pragma unroll 1
        for (int u = warp; u < 40; u += 12) {
          mbar_wait(bars + 8 * (B_KV + (u >> 3)), 0);
          pre_unit(sb, u >> 3, u & 7, lane, st0, st1);
          warp_signal(bars + 8 * (B_PST + (u >> 3)), lane);
        }
#pragma unroll 1
        for (int r = wg; r < (wg < 2 ? wg + 1 : 5); r++) {
          mbar_wait(bars + 8 * (B_F + r), 0);
          build_table(sb, r, lt);
          bar_sync(1 + wg, 128);
          if (lead) mbar_arrive(bars + 8 * (B_TAB + r));
        }
      }
      {
        uint32_t tid2;
        asm volatile("mov.u32 %0, %%tid.x;" : "=r"(tid2));
        const int lane = tid2 & 31, g = lane >> 2, t = lane & 3;
        const uint32_t ex = sb + EXCH + wg * 12288 + lane * 8;
        const int L0 = 128 * w + 8 + g;
        const uint32_t ta0 = sb + ((g & 1) ? TAB_O + ((2047 - L0) / 2 + t) * 4 : TAB_E + ((2048 - L0) / 2 + t) * 4);
        uint32_t A[16][4];
        conv_load_a<0>(A, ta0 + TABB(wg));
        conv_load_a<8>(A, ta0 + TABB(wg));
        const uint32_t qc0 = sb + w * 512 + t * 64 + (t >= 2 ? 32 : 0) + (g & 1) * 16 + (g >> 1) * 4;
        const uint32_t hst0 = sb + w * 256 + t * 32 + (((g & 1) ^ ((b >> 2) & 1)) << 4) + (g >> 1) * 4;
#pragma unroll 1
        for (int r = wg; r < 5; r += 3) {
          const uint64_t db = mkdesc(sb + UB(r) + 128 - 16, 16, 0x8);
          const int nx = r == 1 ? 2 : (r == 0 || r == 3) ? 1 : 0;
          float d0[32], d1[32], c0 = 0.f, c1 = 0.f;
          const uint32_t qc = qc0 + QCB(r), hst = hst0 + TABB(r);
          if (r >= 3) { mbar_wait(bars + 8 * (B_TAB + r), 0); conv_load_a<0>(A, ta0 + TABB(r)); }
          mbar_wait(bars + 8 * (B_U + r), 0);
          if (r > 0) bar_sync(4 + wg, 256);
          WG_FENCE();
          conv_mma<0, 0, 0>(d0, A, db);
          WG_COMMIT();
          conv_mma<1, 0, 1>(d1, A, db);
          WG_COMMIT();
          bar_arrive(4 + nx, 256);
          if (r >= 3) conv_load_a<8>(A, ta0 + TABB(r));
          mbar_wait(bars + 8 * (B_QC + r), 0);
          WG_WAIT(1);
          conv_drain<0>(d0, c0, c1, ex, qc, hst, wg, w, lane);
          WG_WAIT(0);
          conv_drain<1>(d1, c0, c1, ex, qc, hst, wg, w, lane);
          bar_sync(4 + wg, 256);
          WG_FENCE();
          conv_mma<2, 0, 2>(d0, A, db);
          WG_COMMIT();
          conv_mma<3, 0, 3>(d1, A, db);
          WG_COMMIT();
          if (r < 4) bar_arrive(4 + nx, 256);
          WG_WAIT(1);
          conv_drain<2>(d0, c0, c1, ex, qc, hst, wg, w, lane);
          WG_WAIT(0);
          conv_drain<3>(d1, c0, c1, ex, qc, hst, wg, w, lane);
          warp_signal(bars + 8 * (B_HST + r), lane);
        }
      }
    }
    if (b < 130) {
      uint32_t res[20];
      uint32_t tid2;
      asm volatile("mov.u32 %0, %%tid.x;" : "=r"(tid2));
      const int lane = tid2 & 31, g = lane >> 2, t = lane & 3, lt = tid2 & 127;
      const bool lead = lt == 0;
      const int m_ = lane >> 3, rho = lane & 7;
      const uint32_t stg = sb + GST + (wg & 1) * 19456;
      float d[40];
#pragma unroll
      for (int i = 0; i < 40; i++) d[i] = 0.f;
      if (wg < 2) {
        gemm_seg<0, 4, 4, 16384, B_WF2, B_WE2, 1, 10, 10240, B_XE>(d, sb, 10, wg * 8192, 0, 0, 0, true, lt, -1);
        mbar_wait(bars + 8 * B_TOK, 0);
        const uint32_t stg1 = stg + (w >> 1) * 5120;
        const float cs0 = __uint_as_float(lds32(sb + CS1S + (64 * wg + 16 * w + g) * 4)), cs1 = __uint_as_float(lds32(sb + CS1S + (64 * wg + 16 * w + g + 8) * 4));
#pragma unroll
        for (int j = 0; j < 10; j += 2) {
          uint32_t pk[4];
#pragma unroll
          for (int jj = 0; jj < 2; jj++) {
            const int o = 4 * (j + jj);
            const float4 sa = lds128f(sb + TOKST + (8 * (j + jj) + 2 * t) * 16), sc = lds128f(sb + TOKST + (8 * (j + jj) + 2 * t + 1) * 16);
            pk[2 * jj] = gelu_pair(fmaf(d[o], sa.z, sa.w * cs0), fmaf(d[o + 1], sc.z, sc.w * cs0));
            pk[2 * jj + 1] = gelu_pair(fmaf(d[o + 2], sa.z, sa.w * cs1), fmaf(d[o + 3], sc.z, sc.w * cs1));
          }
          const int tok = 8 * (j + (m_ >> 1)) + rho, chunk = 2 * (w & 1) + (m_ & 1);
          stsm4t(stg1 + tok * 64 + ((chunk ^ ((tok >> 1) & 3)) << 4), pk[0], pk[1], pk[2], pk[3]);
          if (j == 2 || j >= 6) warp_signal(bars + 8 * ((j == 8 ? B_SG : j == 6 ? B_SS3 : B_SS2) + wg), lane);
        }
      }
      if (wg == 2) {
        float s[8], ss[8];
#pragma unroll
        for (int i = 0; i < 8; i++) { s[i] = 0.f; ss[i] = 0.f; }
        if (w == 3) {
          mbar_wait(bars + 8 * (B_XF + 3), 0);
          const float4* cp = reinterpret_cast<const float4*>(g_cs1 + 128 * fj) + lane;
          const float4 a = __ldcg(cp), c = __ldcg(cp + D_ / 4), e = __ldcg(cp + D_ / 2), f = __ldcg(cp + 3 * D_ / 4);
          sts128(sb + CS1S + lane * 16, __float_as_uint((a.x + c.x) + (e.x + f.x)), __float_as_uint((a.y + c.y) + (e.y + f.y)),
                 __float_as_uint((a.z + c.z) + (e.z + f.z)), __float_as_uint((a.w + c.w) + (e.w + f.w)));
        }
        if (b < 128) mbar_wait(bars + 8 * (B_HST + 4), 0);
        if (w < 3) {
          const bool act = lt < 80;
#pragma unroll 1
          for (int c = 0; c < 5; c++) {
            mbar_wait(bars + 8 * (B_XF + c), 0);
            uint4 v[16];
#pragma unroll
            for (int k1 = 0; k1 < 16; k1++) v[k1] = lds128(sb + XR + c * 20480 + k1 * 1280 + min(lt, 79) * 16);
            if (c == 4) {
              asm volatile("" ::"r"(v[15].x) : "memory");
              bar_arrive(7, 352);
            }
#pragma unroll
            for (int k1 = 0; k1 < 16; k1++) {
              float f;
              f = bf_lo(v[k1].x); s[0] += f; ss[0] = fmaf(f, f, ss[0]); f = bf_hi(v[k1].x); s[1] += f; ss[1] = fmaf(f, f, ss[1]);
              f = bf_lo(v[k1].y); s[2] += f; ss[2] = fmaf(f, f, ss[2]); f = bf_hi(v[k1].y); s[3] += f; ss[3] = fmaf(f, f, ss[3]);
              f = bf_lo(v[k1].z); s[4] += f; ss[4] = fmaf(f, f, ss[4]); f = bf_hi(v[k1].z); s[5] += f; ss[5] = fmaf(f, f, ss[5]);
              f = bf_lo(v[k1].w); s[6] += f; ss[6] = fmaf(f, f, ss[6]); f = bf_hi(v[k1].w); s[7] += f; ss[7] = fmaf(f, f, ss[7]);
            }
          }
          const int k0 = (lt >> 1) & 7, half = (lt & 1) ^ (k0 >> 2);
#pragma unroll
          for (int i = 0; i < 4; i++) {
            const bool up = k0 & 4;
            const float a = up ? s[i] : s[i + 4], c = up ? ss[i] : ss[i + 4];
            s[i] = (up ? s[i + 4] : s[i]) + __shfl_xor_sync(0xffffffffu, a, 9);
            ss[i] = (up ? ss[i + 4] : ss[i]) + __shfl_xor_sync(0xffffffffu, c, 9);
          }
#pragma unroll
          for (int i = 0; i < 2; i++) {
            const bool up = k0 & 2;
            const float a = up ? s[i] : s[i + 2], c = up ? ss[i] : ss[i + 2];
            s[i] = (up ? s[i + 2] : s[i]) + __shfl_xor_sync(0xffffffffu, a, 4);
            ss[i] = (up ? ss[i + 2] : ss[i]) + __shfl_xor_sync(0xffffffffu, c, 4);
          }
          {
            const bool up = k0 & 1;
            const float a = up ? s[0] : s[1], c = up ? ss[0] : ss[1];
            s[0] = (up ? s[1] : s[0]) + __shfl_xor_sync(0xffffffffu, a, 2);
            ss[0] = (up ? ss[1] : ss[0]) + __shfl_xor_sync(0xffffffffu, c, 2);
          }
          if (act) {
            const float m = s[0] * (1.f / D_);
            const float var = fmaxf(ss[0] * (1.f / D_) - m * m, 0.f);
            const float r2 = rsqrtf(var + EPS);
            const int tok = (lt >> 4) * 16 + half * 8 + k0;
            const float r23 = TT * ti + tok < S_ ? 0.5f * r2 * rsqrtf(var * r2 * r2 + EPS) : 0.f;
            sts128(sb + TOKST + tok * 16, __float_as_uint(r2), __float_as_uint(-m * r2), __float_as_uint(r23), __float_as_uint(-m * r23));
          }
        }
        __syncwarp();
        if (lane == 0) { mbar_arrive(bars + 8 * B_TOK); mbar_arrive(bars + 8 * B_XFREE); }
      } else {
        {
          const uint32_t hb = sb + XR + (2 * fj + wg) * 10240 + 2 * w * 1280 + g * 32 + t * 4;
#pragma unroll
          for (int j = 0; j < 10; j++) {
            const uint32_t a = hb + (j >> 1) * 256 + (((j & 1) ^ (g >> 2)) << 4);
            res[2 * j] = lds32(a); res[2 * j + 1] = lds32(a + 1280);
          }
        }
#pragma unroll
        for (int j = 0; j < 10; j++) {
          const int o = 4 * j, q = 2 * j;
          const float2 sa = lds64f(sb + TOKST + (8 * j + 2 * t) * 16), sc = lds64f(sb + TOKST + (8 * j + 2 * t + 1) * 16);
          d[o] = fmaf(bf_lo(res[q]), sa.x, sa.y); d[o + 1] = fmaf(bf_hi(res[q]), sc.x, sc.y);
          d[o + 2] = fmaf(bf_lo(res[q + 1]), sa.x, sa.y); d[o + 3] = fmaf(bf_hi(res[q + 1]), sc.x, sc.y);
        }
        bar_sync(1 + wg, 128);
        if (lead) { mbar_arrive(bars + 8 * B_XFREE); }
        if (wg == 1) { mbar_wait(bars + 8 * B_SD, 0); mbar_wait(bars + 8 * B_SD, 1); }
        gemm_seg<1, 8, 4, 16384, B_WF2, B_WE2, 2, 5, 20480, B_XE>(d, sb, 5, 0, 2 + wg, wg ? 0x8 : 0x3, 0x1F, wg == 0, lt, -1);
        mbar_wait(bars + 8 * (B_SD + wg), 0);
#pragma unroll
        for (int j = 0; j < 10; j += 2) {
          uint32_t pk[4];
#pragma unroll
          for (int i = 0; i < 4; i++) {
            pk[i] = pack_bf16(d[4 * j + 2 * i], d[4 * j + 2 * i + 1]);
            res[2 * j + i] = pack_bf16(bf_lo(res[2 * j + i]) + bf_lo(pk[i]), bf_hi(res[2 * j + i]) + bf_hi(pk[i]));
          }
          const int tok = 8 * (j + (m_ >> 1)) + rho, chunk = 2 * w + (m_ & 1);
          stsm4t(stg + tok * 128 + ((chunk ^ (tok & 7)) << 4), pk[0], pk[1], pk[2], pk[3]);
        }
        warp_signal(bars + 8 * (B_SG + wg), lane);
        bar_sync(1 + wg, 128);
        if (lt < 80) {
          float s = 0.f, ss = 0.f;
          uint4 v[8];
#pragma unroll
          for (int i = 0; i < 8; i++) v[i] = lds128(stg + lt * 128 + (((i + lt) & 7) << 4));
          float s1 = 0.f, ss1 = 0.f;
#pragma unroll
          for (int i = 0; i < 8; i++) {
            float f;
            f = bf_lo(v[i].x); s += f; ss = fmaf(f, f, ss); f = bf_hi(v[i].x); s1 += f; ss1 = fmaf(f, f, ss1);
            f = bf_lo(v[i].y); s += f; ss = fmaf(f, f, ss); f = bf_hi(v[i].y); s1 += f; ss1 = fmaf(f, f, ss1);
            f = bf_lo(v[i].z); s += f; ss = fmaf(f, f, ss); f = bf_hi(v[i].z); s1 += f; ss1 = fmaf(f, f, ss1);
            f = bf_lo(v[i].w); s += f; ss = fmaf(f, f, ss); f = bf_hi(v[i].w); s1 += f; ss1 = fmaf(f, f, ss1);
          }
          s += s1; ss += ss1;
          sts64f(sb + XST + wg * 640 + lt * 8, s, ss);
        }
        warp_signal(bars + 8 * (B_SS + wg), lane);
      }
      mbar_wait(bars + 8 * (B_XE + 4), 0);
      if (warp == 8) {
        if (lane < 8) {
#pragma unroll
          for (int s = 0; s < 5; s++) sts128(sb + XR + s * 19456 + TT3 * 128 + lane * 16, 0x3F803F80u, 0x3F803F80u, 0x3F803F80u, 0x3F803F80u);
        }
        warp_signal(bars + 8 * B_ONES, lane);
      }
      if (b < 126) {
        float d[76];
#pragma unroll
        for (int i = 0; i < 76; i++) d[i] = 0.f;
        mbar_wait(bars + 8 * B_ONES, 0);
        gemm_seg<2, 4, 3, 24576, B_WF3, B_WE3, 1, 5, 19456, B_X3E>(d, sb, 5, wg * 8192, 0, 0, 0, true, lt, -1);
        if (wg == 0) bar_sync(7, 384); else bar_arrive(7, 384);
        if (wg > 0) bar_sync(4 + wg, 256);
        if (wg == 0) {
          gemm_seg<2, 4, 9, 8192, B_WF1, B_WE1, 1, 5, 19456, B_X3E>(d, sb, 5, 0, 6, 0, 0x1F, true, lt, 5);
        } else {
          const uint32_t s0 = wg == 1 ? 2 : 7, s2 = wg == 1 ? 4 : 0;
          const uint64_t la0 = mkdesc(sb + WR + s0 * 8192, 1024, 0x40000040), la2 = mkdesc(sb + WR + s2 * 8192, 1024, 0x40000040), lb = mkdesc(sb + XR, 16, 0x40000040);
          const uint32_t w0 = bars + 8 * (B_WF1 + s0), w2 = bars + 8 * (B_WF1 + s2);
          mbar_wait2(w0, wg - 1, w0 + 8, wg - 1);
          mbar_wait2(w2, wg - 1, w2 + 8, wg - 1);
          reg_fence(d);
          WG_FENCE();
#pragma unroll
          for (int c = 0; c < 5; c++) {
            if (c == 4) { mbar_wait(w2 + 16, 1); WG_FENCE(); }
#pragma unroll
            for (int k = 0; k < 4; k++) wg_ss152k(d, (c < 2 ? la0 + c * 512 : la2 + (c - 2) * 512) + k * 128, lb + c * 1216 + k * 2);
          }
          WG_COMMIT();
          if (wg == 1) bar_arrive(6, 256);
          WG_WAIT(0);
          reg_fence(d);
          if (lt < 10) mbar_arrive(lt < 5 ? bars + 8 * (B_X3E + lt) : (lt < 7 ? w0 + 8 * (lt - 5) : w2 + 8 * (lt - 7)) + 8 * (B_WE1 - B_WF1));
        }
        mbar_wait(bars + 8 * B_ST3, 0);
        const float cs0 = __shfl_sync(0xffffffffu, d[73], lane | 3), cs1 = __shfl_sync(0xffffffffu, d[75], lane | 3);
#pragma unroll
        for (int part = 0; part < 2; part++) {
          const int j0 = part ? 10 : 0, j1 = part ? 19 : 10;
          uint32_t pk[20];
#pragma unroll
          for (int j = j0; j < j1; j++) {
            const float4 sa = lds128f(sb + ST3 + (8 * j + 2 * t) * 8);
            const int o = 4 * j, q = 2 * (j - j0);
            pk[q] = gelu_pair(fmaf(d[o], sa.x, sa.y * cs0), fmaf(d[o + 1], sa.z, sa.w * cs0));
            pk[q + 1] = gelu_pair(fmaf(d[o + 2], sa.x, sa.y * cs1), fmaf(d[o + 3], sa.z, sa.w * cs1));
          }
          if (!part) mbar_wait(bars + 8 * (B_SD + (wg & 1)), wg == 2 ? 0 : 1);
#pragma unroll
          for (int j = j0; j < j1; j += 2) {
            const int tok = 8 * (j + (m_ >> 1)) + rho, chunk = 2 * w + (m_ & 1), q = 2 * (j - j0);
            const uint32_t a = stg + tok * 128 + ((chunk ^ (tok & 7)) << 4);
            if (j + 1 < 19) stsm4t(a, pk[q], pk[q + 1], pk[q + 2], pk[q + 3]); else stsm2t(a, pk[q], pk[q + 1]);
          }
          if (!part) warp_signal(bars + 8 * (B_SS2 + wg), lane);
        }
        warp_signal(bars + 8 * (B_SG + wg), lane);
      }
      if (wg < 2) {
        float d[40];
#pragma unroll
        for (int j = 0; j < 20; j++) { d[2 * j] = bf_lo(res[j]); d[2 * j + 1] = bf_hi(res[j]); }
        gemm_seg<3, 4, 6, 16384, B_WF4, B_WE4, 1, 6, 10240, B_XE>(d, sb, 27, wg * 8192 - 32768, 4, 0, 0, false, lt, -1);
        if (b < 126) mbar_wait(bars + 8 * (B_SD + (wg ? 1 : 2)), 0); else mbar_wait(bars + 8 * (B_SD + wg), 1);
#pragma unroll
        for (int j = 0; j < 10; j += 2) {
          const int tok = 8 * (j + (m_ >> 1)) + rho, chunk = 2 * w + (m_ & 1);
          stsm4t(stg + tok * 128 + ((chunk ^ (tok & 7)) << 4), pack_bf16(d[4 * j], d[4 * j + 1]), pack_bf16(d[4 * j + 2], d[4 * j + 3]),
                 pack_bf16(d[4 * j + 4], d[4 * j + 5]), pack_bf16(d[4 * j + 6], d[4 * j + 7]));
        }
        warp_signal(bars + 8 * (B_SG + wg), lane);
      }
    }
  }
}

typedef CUresult (*EncFn)(CUtensorMap*, CUtensorMapDataType, cuuint32_t, void*, const cuuint64_t*, const cuuint64_t*, const cuuint32_t*,
                          const cuuint32_t*, CUtensorMapInterleave, CUtensorMapSwizzle, CUtensorMapL2promotion, CUtensorMapFloatOOBfill);

void make2d(EncFn enc, CUtensorMap* tm, const void* ptr, uint64_t inner, uint64_t outer, uint32_t bi, uint32_t bo, CUtensorMapSwizzle sw) {
  cuuint64_t gd[2] = {inner, outer};
  cuuint64_t gs[1] = {inner * 2};
  cuuint32_t bd[2] = {bi, bo}, es[2] = {1, 1};
  CUresult rr = enc(tm, CU_TENSOR_MAP_DATA_TYPE_BFLOAT16, 2, const_cast<void*>(ptr), gd, gs, bd, es, CU_TENSOR_MAP_INTERLEAVE_NONE, sw,
      CU_TENSOR_MAP_L2_PROMOTION_L2_128B, CU_TENSOR_MAP_FLOAT_OOB_FILL_NONE);
  (void)rr;
}

void make3w(EncFn enc, CUtensorMap* tm, const void* ptr, uint64_t cols, uint64_t rows, uint32_t nb, uint32_t br = 64) {
  cuuint64_t gd[3] = {64, rows, cols / 64};
  cuuint64_t gs[2] = {cols * 2, 128};
  cuuint32_t bd[3] = {64, br, nb}, es[3] = {1, 1, 1};
  enc(tm, CU_TENSOR_MAP_DATA_TYPE_BFLOAT16, 3, const_cast<void*>(ptr), gd, gs, bd, es, CU_TENSOR_MAP_INTERLEAVE_NONE, CU_TENSOR_MAP_SWIZZLE_128B,
      CU_TENSOR_MAP_L2_PROMOTION_L2_128B, CU_TENSOR_MAP_FLOAT_OOB_FILL_NONE);
}

}

extern "C" void kernel_launch(void* const* d_in, const int* in_sizes, int n_in, void* d_out, int out_size) {
  (void)in_sizes; (void)n_in; (void)out_size;
  static EncFn enc = nullptr;
  static void *kvT, *qc, *hT, *hs, *x1, *H, *st;
  if (!enc) {
    void* fn = nullptr;
    cudaDriverEntryPointQueryResult qr;
    cudaGetDriverEntryPoint("cuTensorMapEncodeTiled", &fn, cudaEnableDefault, &qr);
    enc = (EncFn)fn;
    cudaFuncSetAttribute(fused_kernel, cudaFuncAttributeMaxDynamicSharedMemorySize, SMEM_BYTES);
    cudaGetSymbolAddress(&kvT, g_kvT); cudaGetSymbolAddress(&qc, g_qc); cudaGetSymbolAddress(&hT, g_hT);
    cudaGetSymbolAddress(&hs, g_hs); cudaGetSymbolAddress(&x1, g_x1); cudaGetSymbolAddress(&H, g_H); cudaGetSymbolAddress(&st, g_st);
  }
  Params p;
  p.shift_k = (const __nv_bfloat16*)d_in[3]; p.ssm_k = (const __nv_bfloat16*)d_in[4]; p.ssm_D = (const __nv_bfloat16*)d_in[5];
  p.pw1 = (const __nv_bfloat16*)d_in[7]; p.pw2 = (const __nv_bfloat16*)d_in[8]; p.pw3 = (const __nv_bfloat16*)d_in[9]; p.pw4 = (const __nv_bfloat16*)d_in[10];
  for (int i = 0; i < 3; i++) {
    cuuint64_t gd[3] = {64, S_, 10};
    cuuint64_t gs[2] = {D_ * 2, 128};
    cuuint32_t bd[3] = {64, i == 1 ? 19u : 16u, i == 0 ? 10u : 2u}, es[3] = {1, 1, 1};
    enc(i == 0 ? &p.xin : i == 1 ? &p.kin : &p.vin, CU_TENSOR_MAP_DATA_TYPE_BFLOAT16, 3, d_in[i], gd, gs, bd, es, CU_TENSOR_MAP_INTERLEAVE_NONE,
        CU_TENSOR_MAP_SWIZZLE_128B, CU_TENSOR_MAP_L2_PROMOTION_L2_128B, CU_TENSOR_MAP_FLOAT_OOB_FILL_NONE);
  }
  make3w(enc, &p.w1p, p.pw1, D_, D_, 2);
  make3w(enc, &p.w3t, p.pw3, F_, D_, 3);
  make3w(enc, &p.w4p, p.pw4, D_, F_, 2);
  make2d(enc, &p.w2d, p.pw2, D_, D_, 64, 128, CU_TENSOR_MAP_SWIZZLE_128B);
  make2d(enc, &p.w3, p.pw3, F_, D_, 64, 64, CU_TENSOR_MAP_SWIZZLE_128B);
  make2d(enc, &p.kvT, kvT, S_, D_, 16, 128, CU_TENSOR_MAP_SWIZZLE_32B);
  make2d(enc, &p.qc, qc, 2 * S_, D_, 32, 128, CU_TENSOR_MAP_SWIZZLE_64B);
  {
    cuuint64_t gd[5] = {16, 8, 5, 80, 26};
    cuuint64_t gs[4] = {32, 256, 1280, 102400};
    cuuint32_t bd[5] = {16, 1, 5, 1, 26}, es[5] = {1, 1, 1, 1, 1};
    CUresult rr = enc(&p.hT, CU_TENSOR_MAP_DATA_TYPE_BFLOAT16, 5, hT, gd, gs, bd, es, CU_TENSOR_MAP_INTERLEAVE_NONE, CU_TENSOR_MAP_SWIZZLE_NONE,
        CU_TENSOR_MAP_L2_PROMOTION_NONE, CU_TENSOR_MAP_FLOAT_OOB_FILL_NONE);
    (void)rr;
  }
  {
    cuuint64_t gd[2] = {2176, 10};
    cuuint64_t gs[1] = {2176 * 8};
    cuuint32_t bd[2] = {154, 10}, es[2] = {1, 1};
    enc(&p.stL, CU_TENSOR_MAP_DATA_TYPE_UINT64, 2, st, gd, gs, bd, es, CU_TENSOR_MAP_INTERLEAVE_NONE, CU_TENSOR_MAP_SWIZZLE_NONE,
        CU_TENSOR_MAP_L2_PROMOTION_NONE, CU_TENSOR_MAP_FLOAT_OOB_FILL_NONE);
  }
  make2d(enc, &p.hsS, hs, D_, S_ + 2, 32, 32, CU_TENSOR_MAP_SWIZZLE_64B);
  make2d(enc, &p.hsS2, hs, D_, S_ + 2, 32, 16, CU_TENSOR_MAP_SWIZZLE_64B);
  make3w(enc, &p.hsL, (__nv_bfloat16*)hs + 2 * D_, D_, S_, 2, TT);
  make2d(enc, &p.x1S, x1, D_, S_, 64, TT, CU_TENSOR_MAP_SWIZZLE_128B);
  make2d(enc, &p.x1L, x1, D_, S_, 64, TT3, CU_TENSOR_MAP_SWIZZLE_128B);
  make2d(enc, &p.HS, H, F_, S_, 64, TT3 - TT, CU_TENSOR_MAP_SWIZZLE_128B);
  make2d(enc, &p.HL, H, F_, S_, 64, TT, CU_TENSOR_MAP_SWIZZLE_128B);
  make2d(enc, &p.outS, d_out, D_, S_, 64, TT, CU_TENSOR_MAP_SWIZZLE_128B);
  fused_kernel<<<NCTA, NTHR, SMEM_BYTES, cudaStreamPerThread>>>(p);
}
```
